```python
import torch

def _softmax(x, axis=-1):
    return torch.softmax(x, dim=axis)
def _gelu(x):
    return torch.nn.functional.gelu(x, approximate="tanh")
def _silu(x):
    return torch.nn.functional.silu(x)
def _sigmoid(x):
    return torch.sigmoid(x)
def _layernorm(x, axis=-1, eps=1e-5):
    m = x.mean(dim=axis, keepdim=True)
    v = x.var(dim=axis, keepdim=True, unbiased=False)
    return (x - m) / torch.sqrt(v + eps)
def _scatter_add(tgt, idx, src, axis=0):
    return tgt.clone().index_add_(axis, idx, src)
def _segment_sum(src, seg, n):
    out = torch.zeros((n,) + src.shape[1:], dtype=src.dtype)
    return out.index_add_(0, seg, src)
def _pad(x, pw):
    flat = tuple(v for pair in reversed(pw) for v in pair)
    return torch.nn.functional.pad(x, flat)

kernel_name = 'gather_scatter__hybrid_graph_tf_graphgps__graph'

def setup_inputs():

    _w = (lambda a: (lambda t: t.to(torch.bfloat16) if t.is_floating_point() else t)(torch.as_tensor(a)))
    N, deg, D = 10000, 16, 256
    E = N * deg
    src = (lambda lo, hi, *s: torch.randint(lo, hi, s))(0, N, E).to(torch.int64)
    dst = (lambda lo, hi, *s: torch.randint(lo, hi, s))(0, N, E).to(torch.int64)
    deg_cnt = torch.bincount(dst, minlength=N).to(float) + 1.0
    sc = 1.0 / float(D) ** 0.5
    return {
        "x": _w((lambda *s: torch.randn(*s, dtype=torch.bfloat16) * 0.05)(N, D)),
        "src": _w(src),
        "dst": _w(dst),
        "deg_inv": _w((1.0 / deg_cnt).to(float)),
        "w_msg": _w((lambda *s: torch.randn(*s, dtype=torch.bfloat16) * 0.2)(D, D) * sc),
        "wq": _w((lambda *s: torch.randn(*s, dtype=torch.bfloat16) * 1.6)(D, D) * sc),
        "wk": _w((lambda *s: torch.randn(*s, dtype=torch.bfloat16) * 1.6)(D, D) * sc),
        "wv": _w((lambda *s: torch.randn(*s, dtype=torch.bfloat16) * 0.2)(D, D) * sc),
        "w_out": _w((lambda *s: torch.randn(*s, dtype=torch.bfloat16) * 0.2)(D, D) * sc),
    }

def reference(x, src, dst, deg_inv, w_msg, wq, wk, wv, w_out):
    N, D = x.shape[0], x.shape[1]
    h = _layernorm(x, axis=-1)
    m_e = torch.einsum('nd,de->ne', h, w_msg)
    h_local = _segment_sum(m_e[src], dst, N) * deg_inv[:, None]
    q = torch.einsum('nd,de->ne', h, wq)
    k = torch.einsum('nd,de->ne', h, wk)
    v = torch.einsum('nd,de->ne', h, wv)
    logits = torch.einsum('id,jd->ij', q, k) / (float(D) ** 0.5)
    attn = _softmax(logits, axis=-1)
    h_global = torch.einsum('ij,jd->id', attn, v)
    y = torch.einsum('nd,de->ne', h_local + h_global, w_out)
    return x + y
```

```cpp
#include <cuda.h>
#include <cuda_runtime.h>
#include <cuda_bf16.h>
#include <stdint.h>

namespace {

constexpr int N_NODES = 10000;
constexpr int N_EDGES = 160000;
constexpr int NQT     = 79;
constexpr int NPAD    = NQT * 128;
constexpr int N16     = N_NODES / 16;
constexpr int NZT     = 157;
constexpr int MAXCTA  = 132;
constexpr int MAXSEG  = 4;
constexpr int MAXSLOT = 160;
constexpr int NFIX    = 8;
constexpr int PART_BYTES = 65536 + 2048;

constexpr int LATE = 4;
constexpr int GATH = 26;
constexpr float GAIN = 320.f;
constexpr float THR = 16.f;
constexpr float OFF = 75.f;
constexpr float HS = 0.5f;
constexpr float OBU = 341.25f;
__host__ __device__ constexpr float pow2i(int e) { return e == 0 ? 1.f : 0.5f * pow2i(e - 1); }
__device__ __forceinline__ float obias() { return (threadIdx.x & 2 ? -OBU : OBU) * (HS * pow2i((int)OFF)); }

constexpr uint32_t SM_Q     = 0;
constexpr uint32_t SM_KV    = 65536;
constexpr uint32_t STAGE_B  = 65536 + 2048;
constexpr uint32_t SM_PAD   = SM_KV + 65536;
constexpr uint32_t SM_X     = SM_KV + STAGE_B + 65536;
constexpr uint32_t SM_BAR   = SM_X + 32768;
constexpr uint32_t SMEM_BYTES = SM_BAR + 512;
constexpr uint32_t B_FULL = 0, B_EMPTY = 16;
constexpr uint32_t B_QFULL = 32, B_QEMPTY = 48;
constexpr uint32_t B_SIG = 64;
constexpr uint32_t B_GO = 80, B_ZE = 120;
constexpr uint32_t B_HSIG = 96;
constexpr uint32_t B_T0 = 112;
constexpr uint32_t B_X = 128, B_LN = 256;
constexpr uint32_t B_PUB = 384, B_GATH = 400, B_LATE = 104;
constexpr uint32_t B_PLAN = 392, S_DYN = 416;
constexpr int NBAR = 51;

constexpr int C_A = 0, C_W = 32, C_H = 64, C_E = 96, C_Z = 128, C_DONE = 192, C_U = 224, F_Q = 256, F_P = 352;
constexpr int F_S = F_P + 2 * MAXSLOT, SYNC_WORDS = F_S + 8 * 26;

struct CtaPlan {
    uint32_t hdr;
    uint32_t slots;
    uint32_t seg[MAXSEG];
    uint32_t ptile;
};
struct Plan {
    CtaPlan c[MAXCTA];
    float base[4];
    uint32_t ipc, magic, ms, qpc;
};

__device__ __align__(1024) uint8_t g_h[NPAD * 512];
__device__ __align__(1024) uint8_t g_q[NPAD * 512];
__device__ __align__(1024) uint8_t g_agg[NPAD * 512];
__device__ __align__(1024) uint8_t g_w[3 * 131072];
__device__ __align__(1024) uint8_t g_part[MAXSLOT * PART_BYTES];
__device__ __align__(128) uint8_t g_xch[MAXCTA * MAXCTA * 128];
__device__ __align__(128) uint32_t g_sync[SYNC_WORDS];


__device__ __forceinline__ void wgmma_ss_n128_t0(float (&d)[64], uint64_t da, uint64_t oa, uint64_t db, uint64_t ob, int scale_d) {
    asm volatile("{\n.reg .pred p;\n.reg .b64 da, db;\nsetp.ne.b32 p, %68, 0;\n"
        "add.s64 da, %64, %65;\nadd.s64 db, %66, %67;\n"
        "wgmma.mma_async.sync.aligned.m64n128k16.f32.bf16.bf16 {"
        "%0, %1, %2, %3, %4, %5, %6, %7, %8, %9, %10, %11, %12, %13, %14, %15, "
        "%16, %17, %18, %19, %20, %21, %22, %23, %24, %25, %26, %27, %28, %29, %30, %31, "
        "%32, %33, %34, %35, %36, %37, %38, %39, %40, %41, %42, %43, %44, %45, %46, %47, "
        "%48, %49, %50, %51, %52, %53, %54, %55, %56, %57, %58, %59, %60, %61, %62, %63"
        "}, da, db, p, 1, 1, 0, 0;\n}\n"
      : "+f"(d[0]), "+f"(d[1]), "+f"(d[2]), "+f"(d[3]), "+f"(d[4]), "+f"(d[5]), "+f"(d[6]), "+f"(d[7]),
        "+f"(d[8]), "+f"(d[9]), "+f"(d[10]), "+f"(d[11]), "+f"(d[12]), "+f"(d[13]), "+f"(d[14]), "+f"(d[15]),
        "+f"(d[16]), "+f"(d[17]), "+f"(d[18]), "+f"(d[19]), "+f"(d[20]), "+f"(d[21]), "+f"(d[22]), "+f"(d[23]),
        "+f"(d[24]), "+f"(d[25]), "+f"(d[26]), "+f"(d[27]), "+f"(d[28]), "+f"(d[29]), "+f"(d[30]), "+f"(d[31]),
        "+f"(d[32]), "+f"(d[33]), "+f"(d[34]), "+f"(d[35]), "+f"(d[36]), "+f"(d[37]), "+f"(d[38]), "+f"(d[39]),
        "+f"(d[40]), "+f"(d[41]), "+f"(d[42]), "+f"(d[43]), "+f"(d[44]), "+f"(d[45]), "+f"(d[46]), "+f"(d[47]),
        "+f"(d[48]), "+f"(d[49]), "+f"(d[50]), "+f"(d[51]), "+f"(d[52]), "+f"(d[53]), "+f"(d[54]), "+f"(d[55]),
        "+f"(d[56]), "+f"(d[57]), "+f"(d[58]), "+f"(d[59]), "+f"(d[60]), "+f"(d[61]), "+f"(d[62]), "+f"(d[63])
      : "l"(da), "l"(oa), "l"(db), "l"(ob), "r"(scale_d));
}
__device__ __forceinline__ void wgmma_ss_n112_t0(float (&d)[64], uint64_t da, uint64_t oa, uint64_t db, uint64_t ob, int scale_d) {
    asm volatile("{\n.reg .pred p;\n.reg .b64 da, db;\nsetp.ne.b32 p, %60, 0;\n"
        "add.s64 da, %56, %57;\nadd.s64 db, %58, %59;\n"
        "wgmma.mma_async.sync.aligned.m64n112k16.f32.bf16.bf16 {"
        "%0, %1, %2, %3, %4, %5, %6, %7, %8, %9, %10, %11, %12, %13, %14, %15, "
        "%16, %17, %18, %19, %20, %21, %22, %23, %24, %25, %26, %27, %28, %29, %30, %31, "
        "%32, %33, %34, %35, %36, %37, %38, %39, %40, %41, %42, %43, %44, %45, %46, %47, "
        "%48, %49, %50, %51, %52, %53, %54, %55"
        "}, da, db, p, 1, 1, 0, 0;\n}\n"
      : "+f"(d[0]), "+f"(d[1]), "+f"(d[2]), "+f"(d[3]), "+f"(d[4]), "+f"(d[5]), "+f"(d[6]), "+f"(d[7]),
        "+f"(d[8]), "+f"(d[9]), "+f"(d[10]), "+f"(d[11]), "+f"(d[12]), "+f"(d[13]), "+f"(d[14]), "+f"(d[15]),
        "+f"(d[16]), "+f"(d[17]), "+f"(d[18]), "+f"(d[19]), "+f"(d[20]), "+f"(d[21]), "+f"(d[22]), "+f"(d[23]),
        "+f"(d[24]), "+f"(d[25]), "+f"(d[26]), "+f"(d[27]), "+f"(d[28]), "+f"(d[29]), "+f"(d[30]), "+f"(d[31]),
        "+f"(d[32]), "+f"(d[33]), "+f"(d[34]), "+f"(d[35]), "+f"(d[36]), "+f"(d[37]), "+f"(d[38]), "+f"(d[39]),
        "+f"(d[40]), "+f"(d[41]), "+f"(d[42]), "+f"(d[43]), "+f"(d[44]), "+f"(d[45]), "+f"(d[46]), "+f"(d[47]),
        "+f"(d[48]), "+f"(d[49]), "+f"(d[50]), "+f"(d[51]), "+f"(d[52]), "+f"(d[53]), "+f"(d[54]), "+f"(d[55])
      : "l"(da), "l"(oa), "l"(db), "l"(ob), "r"(scale_d));
}
__device__ __forceinline__ void wgmma_ss_n256_t1(float (&d)[128], uint64_t da, uint64_t oa, uint64_t db, uint64_t ob, int scale_d) {
    asm volatile("{\n.reg .pred p;\n.reg .b64 da, db;\nsetp.ne.b32 p, %132, 0;\n"
        "add.s64 da, %128, %129;\nadd.s64 db, %130, %131;\n"
        "wgmma.mma_async.sync.aligned.m64n256k16.f32.bf16.bf16 {"
        "%0, %1, %2, %3, %4, %5, %6, %7, %8, %9, %10, %11, %12, %13, %14, %15, "
        "%16, %17, %18, %19, %20, %21, %22, %23, %24, %25, %26, %27, %28, %29, %30, %31, "
        "%32, %33, %34, %35, %36, %37, %38, %39, %40, %41, %42, %43, %44, %45, %46, %47, "
        "%48, %49, %50, %51, %52, %53, %54, %55, %56, %57, %58, %59, %60, %61, %62, %63, "
        "%64, %65, %66, %67, %68, %69, %70, %71, %72, %73, %74, %75, %76, %77, %78, %79, "
        "%80, %81, %82, %83, %84, %85, %86, %87, %88, %89, %90, %91, %92, %93, %94, %95, "
        "%96, %97, %98, %99, %100, %101, %102, %103, %104, %105, %106, %107, %108, %109, %110, %111, "
        "%112, %113, %114, %115, %116, %117, %118, %119, %120, %121, %122, %123, %124, %125, %126, %127"
        "}, da, db, p, 1, 1, 0, 1;\n}\n"
      : "+f"(d[0]), "+f"(d[1]), "+f"(d[2]), "+f"(d[3]), "+f"(d[4]), "+f"(d[5]), "+f"(d[6]), "+f"(d[7]),
        "+f"(d[8]), "+f"(d[9]), "+f"(d[10]), "+f"(d[11]), "+f"(d[12]), "+f"(d[13]), "+f"(d[14]), "+f"(d[15]),
        "+f"(d[16]), "+f"(d[17]), "+f"(d[18]), "+f"(d[19]), "+f"(d[20]), "+f"(d[21]), "+f"(d[22]), "+f"(d[23]),
        "+f"(d[24]), "+f"(d[25]), "+f"(d[26]), "+f"(d[27]), "+f"(d[28]), "+f"(d[29]), "+f"(d[30]), "+f"(d[31]),
        "+f"(d[32]), "+f"(d[33]), "+f"(d[34]), "+f"(d[35]), "+f"(d[36]), "+f"(d[37]), "+f"(d[38]), "+f"(d[39]),
        "+f"(d[40]), "+f"(d[41]), "+f"(d[42]), "+f"(d[43]), "+f"(d[44]), "+f"(d[45]), "+f"(d[46]), "+f"(d[47]),
        "+f"(d[48]), "+f"(d[49]), "+f"(d[50]), "+f"(d[51]), "+f"(d[52]), "+f"(d[53]), "+f"(d[54]), "+f"(d[55]),
        "+f"(d[56]), "+f"(d[57]), "+f"(d[58]), "+f"(d[59]), "+f"(d[60]), "+f"(d[61]), "+f"(d[62]), "+f"(d[63]),
        "+f"(d[64]), "+f"(d[65]), "+f"(d[66]), "+f"(d[67]), "+f"(d[68]), "+f"(d[69]), "+f"(d[70]), "+f"(d[71]),
        "+f"(d[72]), "+f"(d[73]), "+f"(d[74]), "+f"(d[75]), "+f"(d[76]), "+f"(d[77]), "+f"(d[78]), "+f"(d[79]),
        "+f"(d[80]), "+f"(d[81]), "+f"(d[82]), "+f"(d[83]), "+f"(d[84]), "+f"(d[85]), "+f"(d[86]), "+f"(d[87]),
        "+f"(d[88]), "+f"(d[89]), "+f"(d[90]), "+f"(d[91]), "+f"(d[92]), "+f"(d[93]), "+f"(d[94]), "+f"(d[95]),
        "+f"(d[96]), "+f"(d[97]), "+f"(d[98]), "+f"(d[99]), "+f"(d[100]), "+f"(d[101]), "+f"(d[102]), "+f"(d[103]),
        "+f"(d[104]), "+f"(d[105]), "+f"(d[106]), "+f"(d[107]), "+f"(d[108]), "+f"(d[109]), "+f"(d[110]), "+f"(d[111]),
        "+f"(d[112]), "+f"(d[113]), "+f"(d[114]), "+f"(d[115]), "+f"(d[116]), "+f"(d[117]), "+f"(d[118]), "+f"(d[119]),
        "+f"(d[120]), "+f"(d[121]), "+f"(d[122]), "+f"(d[123]), "+f"(d[124]), "+f"(d[125]), "+f"(d[126]), "+f"(d[127])
      : "l"(da), "l"(oa), "l"(db), "l"(ob), "r"(scale_d));
}
__device__ __forceinline__ void wgmma_rs_n256_t1(float (&d)[128], uint32_t a0, uint32_t a1, uint32_t a2, uint32_t a3, uint64_t db, uint64_t ob, int scale_d) {
    asm volatile("{\n.reg .pred p;\n.reg .b64 db;\nsetp.ne.b32 p, %134, 0;\n"
        "add.s64 db, %132, %133;\n"
        "wgmma.mma_async.sync.aligned.m64n256k16.f32.bf16.bf16 {"
        "%0, %1, %2, %3, %4, %5, %6, %7, %8, %9, %10, %11, %12, %13, %14, %15, "
        "%16, %17, %18, %19, %20, %21, %22, %23, %24, %25, %26, %27, %28, %29, %30, %31, "
        "%32, %33, %34, %35, %36, %37, %38, %39, %40, %41, %42, %43, %44, %45, %46, %47, "
        "%48, %49, %50, %51, %52, %53, %54, %55, %56, %57, %58, %59, %60, %61, %62, %63, "
        "%64, %65, %66, %67, %68, %69, %70, %71, %72, %73, %74, %75, %76, %77, %78, %79, "
        "%80, %81, %82, %83, %84, %85, %86, %87, %88, %89, %90, %91, %92, %93, %94, %95, "
        "%96, %97, %98, %99, %100, %101, %102, %103, %104, %105, %106, %107, %108, %109, %110, %111, "
        "%112, %113, %114, %115, %116, %117, %118, %119, %120, %121, %122, %123, %124, %125, %126, %127"
        "}, {%128, %129, %130, %131}, db, p, 1, 1, 1;\n}\n"
      : "+f"(d[0]), "+f"(d[1]), "+f"(d[2]), "+f"(d[3]), "+f"(d[4]), "+f"(d[5]), "+f"(d[6]), "+f"(d[7]),
        "+f"(d[8]), "+f"(d[9]), "+f"(d[10]), "+f"(d[11]), "+f"(d[12]), "+f"(d[13]), "+f"(d[14]), "+f"(d[15]),
        "+f"(d[16]), "+f"(d[17]), "+f"(d[18]), "+f"(d[19]), "+f"(d[20]), "+f"(d[21]), "+f"(d[22]), "+f"(d[23]),
        "+f"(d[24]), "+f"(d[25]), "+f"(d[26]), "+f"(d[27]), "+f"(d[28]), "+f"(d[29]), "+f"(d[30]), "+f"(d[31]),
        "+f"(d[32]), "+f"(d[33]), "+f"(d[34]), "+f"(d[35]), "+f"(d[36]), "+f"(d[37]), "+f"(d[38]), "+f"(d[39]),
        "+f"(d[40]), "+f"(d[41]), "+f"(d[42]), "+f"(d[43]), "+f"(d[44]), "+f"(d[45]), "+f"(d[46]), "+f"(d[47]),
        "+f"(d[48]), "+f"(d[49]), "+f"(d[50]), "+f"(d[51]), "+f"(d[52]), "+f"(d[53]), "+f"(d[54]), "+f"(d[55]),
        "+f"(d[56]), "+f"(d[57]), "+f"(d[58]), "+f"(d[59]), "+f"(d[60]), "+f"(d[61]), "+f"(d[62]), "+f"(d[63]),
        "+f"(d[64]), "+f"(d[65]), "+f"(d[66]), "+f"(d[67]), "+f"(d[68]), "+f"(d[69]), "+f"(d[70]), "+f"(d[71]),
        "+f"(d[72]), "+f"(d[73]), "+f"(d[74]), "+f"(d[75]), "+f"(d[76]), "+f"(d[77]), "+f"(d[78]), "+f"(d[79]),
        "+f"(d[80]), "+f"(d[81]), "+f"(d[82]), "+f"(d[83]), "+f"(d[84]), "+f"(d[85]), "+f"(d[86]), "+f"(d[87]),
        "+f"(d[88]), "+f"(d[89]), "+f"(d[90]), "+f"(d[91]), "+f"(d[92]), "+f"(d[93]), "+f"(d[94]), "+f"(d[95]),
        "+f"(d[96]), "+f"(d[97]), "+f"(d[98]), "+f"(d[99]), "+f"(d[100]), "+f"(d[101]), "+f"(d[102]), "+f"(d[103]),
        "+f"(d[104]), "+f"(d[105]), "+f"(d[106]), "+f"(d[107]), "+f"(d[108]), "+f"(d[109]), "+f"(d[110]), "+f"(d[111]),
        "+f"(d[112]), "+f"(d[113]), "+f"(d[114]), "+f"(d[115]), "+f"(d[116]), "+f"(d[117]), "+f"(d[118]), "+f"(d[119]),
        "+f"(d[120]), "+f"(d[121]), "+f"(d[122]), "+f"(d[123]), "+f"(d[124]), "+f"(d[125]), "+f"(d[126]), "+f"(d[127])
      : "r"(a0), "r"(a1), "r"(a2), "r"(a3), "l"(db), "l"(ob), "r"(scale_d));
}
__device__ __forceinline__ void wgmma_rs_n128_t1(float (&d)[64], uint32_t a0, uint32_t a1, uint32_t a2, uint32_t a3, uint64_t db, uint64_t ob, int scale_d) {
    asm volatile("{\n.reg .pred p;\n.reg .b64 db;\nsetp.ne.b32 p, %70, 0;\n"
        "add.s64 db, %68, %69;\n"
        "wgmma.mma_async.sync.aligned.m64n128k16.f32.bf16.bf16 {"
        "%0, %1, %2, %3, %4, %5, %6, %7, %8, %9, %10, %11, %12, %13, %14, %15, "
        "%16, %17, %18, %19, %20, %21, %22, %23, %24, %25, %26, %27, %28, %29, %30, %31, "
        "%32, %33, %34, %35, %36, %37, %38, %39, %40, %41, %42, %43, %44, %45, %46, %47, "
        "%48, %49, %50, %51, %52, %53, %54, %55, %56, %57, %58, %59, %60, %61, %62, %63"
        "}, {%64, %65, %66, %67}, db, p, 1, 1, 1;\n}\n"
      : "+f"(d[0]), "+f"(d[1]), "+f"(d[2]), "+f"(d[3]), "+f"(d[4]), "+f"(d[5]), "+f"(d[6]), "+f"(d[7]),
        "+f"(d[8]), "+f"(d[9]), "+f"(d[10]), "+f"(d[11]), "+f"(d[12]), "+f"(d[13]), "+f"(d[14]), "+f"(d[15]),
        "+f"(d[16]), "+f"(d[17]), "+f"(d[18]), "+f"(d[19]), "+f"(d[20]), "+f"(d[21]), "+f"(d[22]), "+f"(d[23]),
        "+f"(d[24]), "+f"(d[25]), "+f"(d[26]), "+f"(d[27]), "+f"(d[28]), "+f"(d[29]), "+f"(d[30]), "+f"(d[31]),
        "+f"(d[32]), "+f"(d[33]), "+f"(d[34]), "+f"(d[35]), "+f"(d[36]), "+f"(d[37]), "+f"(d[38]), "+f"(d[39]),
        "+f"(d[40]), "+f"(d[41]), "+f"(d[42]), "+f"(d[43]), "+f"(d[44]), "+f"(d[45]), "+f"(d[46]), "+f"(d[47]),
        "+f"(d[48]), "+f"(d[49]), "+f"(d[50]), "+f"(d[51]), "+f"(d[52]), "+f"(d[53]), "+f"(d[54]), "+f"(d[55]),
        "+f"(d[56]), "+f"(d[57]), "+f"(d[58]), "+f"(d[59]), "+f"(d[60]), "+f"(d[61]), "+f"(d[62]), "+f"(d[63])
      : "r"(a0), "r"(a1), "r"(a2), "r"(a3), "l"(db), "l"(ob), "r"(scale_d));
}
__device__ __forceinline__ void wgmma_ss_n32_t0(float (&d)[16], uint64_t da, uint64_t oa, uint64_t db, uint64_t ob, int scale_d) {
    asm volatile("{\n.reg .pred p;\n.reg .b64 da, db;\nsetp.ne.b32 p, %20, 0;\n"
        "add.s64 da, %16, %17;\nadd.s64 db, %18, %19;\n"
        "wgmma.mma_async.sync.aligned.m64n32k16.f32.bf16.bf16 {"
        "%0, %1, %2, %3, %4, %5, %6, %7, %8, %9, %10, %11, %12, %13, %14, %15"
        "}, da, db, p, 1, 1, 0, 0;\n}\n"
      : "+f"(d[0]), "+f"(d[1]), "+f"(d[2]), "+f"(d[3]), "+f"(d[4]), "+f"(d[5]), "+f"(d[6]), "+f"(d[7]),
        "+f"(d[8]), "+f"(d[9]), "+f"(d[10]), "+f"(d[11]), "+f"(d[12]), "+f"(d[13]), "+f"(d[14]), "+f"(d[15])
      : "l"(da), "l"(oa), "l"(db), "l"(ob), "r"(scale_d));
}
__device__ __forceinline__ void wgmma_ss_n32_t1(float (&d)[16], uint64_t da, uint64_t oa, uint64_t db, uint64_t ob, int scale_d) {
    asm volatile("{\n.reg .pred p;\n.reg .b64 da, db;\nsetp.ne.b32 p, %20, 0;\n"
        "add.s64 da, %16, %17;\nadd.s64 db, %18, %19;\n"
        "wgmma.mma_async.sync.aligned.m64n32k16.f32.bf16.bf16 {"
        "%0, %1, %2, %3, %4, %5, %6, %7, %8, %9, %10, %11, %12, %13, %14, %15"
        "}, da, db, p, 1, 1, 0, 1;\n}\n"
      : "+f"(d[0]), "+f"(d[1]), "+f"(d[2]), "+f"(d[3]), "+f"(d[4]), "+f"(d[5]), "+f"(d[6]), "+f"(d[7]),
        "+f"(d[8]), "+f"(d[9]), "+f"(d[10]), "+f"(d[11]), "+f"(d[12]), "+f"(d[13]), "+f"(d[14]), "+f"(d[15])
      : "l"(da), "l"(oa), "l"(db), "l"(ob), "r"(scale_d));
}

__device__ __forceinline__ uint32_t smem_u32(const void* p) { return (uint32_t)__cvta_generic_to_shared(p); }
__device__ __forceinline__ bool elect_one() {
    uint32_t e;
    asm volatile("{\n.reg .pred p;\nelect.sync _|p, 0xffffffff;\nselp.u32 %0, 1, 0, p;\n}\n" : "=r"(e));
    return e;
}
__device__ __forceinline__ void mbar_init(uint32_t bar, uint32_t cnt) { asm volatile("mbarrier.init.shared::cta.b64 [%0], %1;" :: "r"(bar), "r"(cnt) : "memory"); }
__device__ __forceinline__ void mbar_expect_tx(uint32_t bar, uint32_t bytes) { asm volatile("mbarrier.arrive.expect_tx.shared::cta.b64 _, [%0], %1;" :: "r"(bar), "r"(bytes) : "memory"); }
__device__ __forceinline__ void mbar_arrive(uint32_t bar) { asm volatile("mbarrier.arrive.shared::cta.b64 _, [%0];" :: "r"(bar) : "memory"); }
__device__ __forceinline__ void mbar_wait(uint32_t bar, uint32_t parity) {
    asm volatile("{\n.reg .pred p;\n.reg .u32 c;\nmov.u32 c, 0;\n"
        "LAB_WAIT:\n"
        "mbarrier.try_wait.parity.shared::cta.b64 p, [%0], %1;\n"
        "@p bra LAB_DONE;\n"
        "add.u32 c, c, 1;\n"
        "setp.lt.u32 p, c, 33554432;\n"
        "@p bra LAB_WAIT;\n"
        "trap;\n"
        "LAB_DONE:\n}\n" :: "r"(bar), "r"(parity) : "memory");
}
__device__ __forceinline__ void poll_ge(const uint32_t* p, uint32_t target) {
    asm volatile("{\n.reg .pred p;\n.reg .u32 c, v;\nmov.u32 c, 0;\n"
        "LAB_POLL:\n"
        "ld.acquire.gpu.global.u32 v, [%0];\n"
        "setp.ge.u32 p, v, %1;\n"
        "@p bra LAB_PDONE;\n"
        "add.u32 c, c, 1;\n"
        "setp.lt.u32 p, c, 8388608;\n"
        "@p bra LAB_POLL;\n"
        "trap;\n"
        "LAB_PDONE:\n}\n" :: "l"(p), "r"(target) : "memory");
}
__device__ __forceinline__ void poll_ge_slow(const uint32_t* p, uint32_t target) {
    asm volatile("{\n.reg .pred p;\n.reg .u32 c, v;\nmov.u32 c, 0;\n"
        "LAB_POLL:\n"
        "ld.relaxed.gpu.global.u32 v, [%0];\n"
        "setp.ge.u32 p, v, %1;\n"
        "@p bra LAB_PDONE;\n"
        "nanosleep.u32 400;\n"
        "add.u32 c, c, 1;\n"
        "setp.lt.u32 p, c, 8388608;\n"
        "@p bra LAB_POLL;\n"
        "trap;\n"
        "LAB_PDONE:\n"
        "ld.acquire.gpu.global.u32 v, [%0];\n}\n" :: "l"(p), "r"(target) : "memory");
}
__device__ __forceinline__ void red_add(uint32_t* p) { asm volatile("red.relaxed.gpu.global.add.u32 [%0], 1;" :: "l"(p) : "memory"); }
__device__ __forceinline__ void fence_gpu() { asm volatile("fence.acq_rel.gpu;" ::: "memory"); }
__device__ __forceinline__ void signal_add(uint32_t* p) { fence_gpu(); if (elect_one()) red_add(p); }
__device__ __forceinline__ void fence_async_global() { asm volatile("fence.proxy.async.global;" ::: "memory"); }
__device__ __forceinline__ void fence_async_smem() { asm volatile("fence.proxy.async.shared::cta;" ::: "memory"); }
__device__ __forceinline__ void bulk_g2s(uint32_t dst, const void* src, uint32_t bytes, uint32_t bar) {
    asm volatile("cp.async.bulk.shared::cluster.global.mbarrier::complete_tx::bytes [%0], [%1], %2, [%3];" :: "r"(dst), "l"(src), "r"(bytes), "r"(bar) : "memory");
}
__device__ __forceinline__ void bulk_s2g(void* dst, uint32_t src, uint32_t bytes) {
    asm volatile("cp.async.bulk.global.shared::cta.bulk_group [%0], [%1], %2;" :: "l"(dst), "r"(src), "r"(bytes) : "memory");
}
__device__ __forceinline__ void tma_red_add(const CUtensorMap* map, uint32_t src, int row, int col) {
    asm volatile("cp.reduce.async.bulk.tensor.2d.global.shared::cta.add.tile.bulk_group [%0, {%3, %2}], [%1];" :: "l"(map), "r"(src), "r"(row), "r"(col) : "memory");
}
__device__ __forceinline__ void bulk_commit() { asm volatile("cp.async.bulk.commit_group;" ::: "memory"); }
__device__ __forceinline__ void bulk_wait_all() { asm volatile("cp.async.bulk.wait_group 0;" ::: "memory"); }
__device__ __forceinline__ void cp_async16(uint32_t dst, const void* src) { asm volatile("cp.async.cg.shared.global [%0], [%1], 16;" :: "r"(dst), "l"(src) : "memory"); }
__device__ __forceinline__ void cp_async16_zfill(uint32_t dst, const void* src, uint32_t n) {
    asm volatile("cp.async.cg.shared.global [%0], [%1], 16, %2;" :: "r"(dst), "l"(src), "r"(n) : "memory");
}
__device__ __forceinline__ uint32_t atoms_inc(uint32_t a) {
    uint32_t v;
    asm volatile("atom.relaxed.cta.shared.add.u32 %0, [%1], 1;" : "=r"(v) : "r"(a) : "memory");
    return v;
}
__device__ __forceinline__ void sts32(uint32_t a, uint32_t v) { asm volatile("st.shared.u32 [%0], %1;" :: "r"(a), "r"(v) : "memory"); }
__device__ __forceinline__ void sts16(uint32_t a, uint32_t v) { asm volatile("st.shared.u16 [%0], %1;" :: "r"(a), "r"(v) : "memory"); }
__device__ __forceinline__ uint32_t node_of(uint32_t i) { return (i & ~15u) | ((i >> 1) & 7) | ((i & 1) << 3); }
__device__ __forceinline__ uint32_t index_of(uint32_t n) { return (n & ~15u) | ((n & 7) << 1) | ((n >> 3) & 1); }
__device__ __forceinline__ void wg_fence() { asm volatile("wgmma.fence.sync.aligned;" ::: "memory"); }
__device__ __forceinline__ void wg_commit() { asm volatile("wgmma.commit_group.sync.aligned;" ::: "memory"); }
__device__ __forceinline__ void wg_wait0() { asm volatile("wgmma.wait_group.sync.aligned 0;" ::: "memory"); }
__device__ __forceinline__ void bar_sync(int id, int n) { asm volatile("bar.sync %0, %1;" :: "r"(id), "r"(n) : "memory"); }
__device__ __forceinline__ void bar_arrive(int id, int n) { asm volatile("bar.arrive %0, %1;" :: "r"(id), "r"(n) : "memory"); }
__device__ __forceinline__ float ex2(float x) { float y; asm("ex2.approx.ftz.f32 %0, %1;" : "=f"(y) : "f"(x)); return y; }
__device__ __forceinline__ float rcp(float x) { float y; asm("rcp.approx.ftz.f32 %0, %1;" : "=f"(y) : "f"(x)); return y; }
__device__ __forceinline__ float sqrt_approx(float x) { float y; asm("sqrt.approx.ftz.f32 %0, %1;" : "=f"(y) : "f"(x)); return y; }
__device__ __forceinline__ uint32_t pack_bf16(float lo, float hi) { uint32_t r; asm("cvt.rn.bf16x2.f32 %0, %1, %2;" : "=r"(r) : "f"(hi), "f"(lo)); return r; }
__device__ __forceinline__ uint32_t add_bf16x2(uint32_t a, uint32_t b) { uint32_t r; asm("add.rn.bf16x2 %0, %1, %2;" : "=r"(r) : "r"(a), "r"(b)); return r; }
__device__ __forceinline__ uint32_t mul_bf16x2(uint32_t a, uint32_t b) { uint32_t r; asm("mul.rn.bf16x2 %0, %1, %2;" : "=r"(r) : "r"(a), "r"(b)); return r; }
__device__ __forceinline__ uint32_t fma_bf16x2(uint32_t a, uint32_t b, uint32_t c) { uint32_t r; asm("fma.rn.bf16x2 %0, %1, %2, %3;" : "=r"(r) : "r"(a), "r"(b), "r"(c)); return r; }
__device__ __forceinline__ float round_bf16(float v) { return __uint_as_float(pack_bf16(0.f, v)); }
__device__ __forceinline__ float bf_lo(uint32_t w) { return __uint_as_float(w << 16); }
__device__ __forceinline__ float bf_hi(uint32_t w) { return __uint_as_float(w & 0xffff0000u); }
__device__ __forceinline__ void swap_chunk(float* o, uint4* dst, const uint4* src, bool ld, float bias) {
    asm volatile("{\n.reg .pred p;\nsetp.ne.u32 p, %10, 0;\n"
        "st.global.cg.v4.b32 [%8], {%4, %5, %6, %7};\n"
        "@p ld.global.cg.v4.f32 {%0, %1, %2, %3}, [%9];\n}\n"
        : "+f"(o[0]), "+f"(o[1]), "+f"(o[2]), "+f"(o[3])
        : "r"(pack_bf16(o[0] - bias, o[1] - bias)), "r"(pack_bf16(o[2] - bias, o[3] - bias)), "r"(pack_bf16(o[4] - bias, o[5] - bias)),
          "r"(pack_bf16(o[6] - bias, o[7] - bias)), "l"(dst), "l"(src), "r"((uint32_t)ld) : "memory");
}
__device__ __forceinline__ void unpack_chunk(float* o, float bias) {
    asm volatile("{\n.reg .b32 w, t;\n"
        "mov.b32 w, %3;\nand.b32 t, w, 0xffff0000;\nadd.f32 %7, t, %8;\nshl.b32 t, w, 16;\nadd.f32 %6, t, %8;\n"
        "mov.b32 w, %2;\nand.b32 t, w, 0xffff0000;\nadd.f32 %5, t, %8;\nshl.b32 t, w, 16;\nadd.f32 %4, t, %8;\n"
        "mov.b32 w, %1;\nand.b32 t, w, 0xffff0000;\nadd.f32 %3, t, %8;\nshl.b32 t, w, 16;\nadd.f32 %2, t, %8;\n"
        "mov.b32 w, %0;\nand.b32 t, w, 0xffff0000;\nadd.f32 %1, t, %8;\nshl.b32 t, w, 16;\nadd.f32 %0, t, %8;\n}\n"
        : "+f"(o[0]), "+f"(o[1]), "+f"(o[2]), "+f"(o[3]), "+f"(o[4]), "+f"(o[5]), "+f"(o[6]), "+f"(o[7]) : "f"(bias) : "memory");
}
__device__ __forceinline__ void acc_bf16(float (&a)[8], const uint4 v) {
    a[0] += bf_lo(v.x); a[1] += bf_hi(v.x); a[2] += bf_lo(v.y); a[3] += bf_hi(v.y);
    a[4] += bf_lo(v.z); a[5] += bf_hi(v.z); a[6] += bf_lo(v.w); a[7] += bf_hi(v.w);
}
__device__ __forceinline__ uint4 add4(const uint4 a, const uint4 b) {
    return make_uint4(add_bf16x2(a.x, b.x), add_bf16x2(a.y, b.y), add_bf16x2(a.z, b.z), add_bf16x2(a.w, b.w));
}
__device__ __forceinline__ uint32_t lds16(uint32_t a) { uint32_t v; asm volatile("ld.shared.u16 %0, [%1];" : "=r"(v) : "r"(a) : "memory"); return v; }
__device__ __forceinline__ uint32_t lds32(uint32_t a) { uint32_t v; asm volatile("ld.shared.u32 %0, [%1];" : "=r"(v) : "r"(a) : "memory"); return v; }
__device__ __forceinline__ uint4 lds128(uint32_t a) {
    uint4 v;
    asm volatile("ld.shared.v4.u32 {%0, %1, %2, %3}, [%4];" : "=r"(v.x), "=r"(v.y), "=r"(v.z), "=r"(v.w) : "r"(a) : "memory");
    return v;
}
__device__ __forceinline__ void stsm4(uint32_t addr, uint32_t r0, uint32_t r1, uint32_t r2, uint32_t r3) {
    asm volatile("stmatrix.sync.aligned.m8n8.x4.shared.b16 [%0], {%1, %2, %3, %4};" :: "r"(addr), "r"(r0), "r"(r1), "r"(r2), "r"(r3) : "memory");
}
__device__ __forceinline__ const void* at(const void* p, uint32_t off) {
    asm volatile("" : "+r"(off));
    return (const uint8_t*)p + off;
}
__device__ __forceinline__ uint4 ld_cg16(const void* p) { return __ldcg((const uint4*)p); }
template <int N> __device__ __forceinline__ void fence_regs(float (&d)[N]) {
#pragma unroll
    for (int i = 0; i < N; i++) asm volatile("" : "+f"(d[i]) :: "memory");
}
__device__ __forceinline__ uint64_t desc64(uint32_t lo, uint32_t sbo = 4096) { return (uint64_t)(0x40000000u | sbo >> 4) << 32 | lo; }
__device__ __forceinline__ uint32_t make_desc(uint32_t addr, uint32_t lbo) { return ((addr & 0x3FFFF) >> 4) | ((lbo >> 4) << 16); }
__device__ __forceinline__ uint32_t sw_unit(uint32_t row, uint32_t unit  ) {
    return (row >> 3) * 4096 + (unit >> 3) * 1024 + (row & 7) * 128 + (((unit & 7) ^ (row & 7)) << 4);
}
__device__ __forceinline__ constexpr uint32_t koff(int kk) { return ((kk >> 2) * 1024 + (kk & 3) * 32) >> 4; }

template <int K> __device__ __forceinline__ void sched_fence(int nonneg) {
    asm volatile("{\n.reg .pred p;\nsetp.ne.s32 p, %0, %1;\n@p bra LAB_OK;\nLAB_NO:\nnanosleep.u32 %2;\nbra LAB_NO;\nLAB_OK:\n}\n"
                 :: "r"(nonneg), "n"(-K), "n"(K) : "memory");
}
__device__ __forceinline__ void pause() { asm volatile("nanosleep.u32 16;" ::: "memory"); }
__device__ __forceinline__ float quad_max(float v) {
    v = fmaxf(v, __shfl_xor_sync(0xffffffffu, v, 1));
    return fmaxf(v, __shfl_xor_sync(0xffffffffu, v, 2));
}
__device__ __forceinline__ float quad_sum(float v) {
    v += __shfl_xor_sync(0xffffffffu, v, 1);
    return v + __shfl_xor_sync(0xffffffffu, v, 2);
}
template <int K0, int K1>
__device__ __forceinline__ void exp_steps(const float (&S)[64], uint32_t (&P)[32], float& l0, float& l1) {
#pragma unroll
    for (int i = K0 * 8; i < K1 * 8; i += 4) {
        const float p0 = ex2(S[i]), p1 = ex2(S[i + 1]), p2 = ex2(S[i + 2]), p3 = ex2(S[i + 3]);
        l0 += p0 + p1; l1 += p2 + p3;
        P[i / 2] = pack_bf16(p0, p1);
        P[i / 2 + 1] = pack_bf16(p2, p3);
    }
#pragma unroll
    for (int i = K0 * 4; i < K1 * 4; i++) asm volatile("" : "+r"(P[i]) :: "memory");
}
template <int K0, int K1>
__device__ __forceinline__ void pv_steps(float (&O)[128], const uint32_t (&P)[32], uint32_t dV) {
    wg_fence();
#pragma unroll
    for (int kk = K0; kk < K1; kk++) wgmma_rs_n256_t1(O, P[4 * kk], P[4 * kk + 1], P[4 * kk + 2], P[4 * kk + 3], desc64(dV), kk * 512, 1);
}

__device__ __forceinline__ void rescale(float (&O)[128], float a0, float a1) {
    const float b0 = obias() * (1.f - a0), b1 = obias() * (1.f - a1);
#pragma unroll
    for (int i = 0; i < 128; i += 4) {
        O[i] = fmaf(O[i], a0, b0); O[i + 1] = fmaf(O[i + 1], a0, b0); O[i + 2] = fmaf(O[i + 2], a1, b1); O[i + 3] = fmaf(O[i + 3], a1, b1);
    }
}
template <int K>
__device__ __forceinline__ void swap_steps(float (&O)[128], float (&S)[64], uint32_t dQ, uint32_t dK, uint4* pd, const uint4* ps, bool ld, int opaque) {
    swap_chunk(&O[8 * K], pd + K * 128, ps + K * 128, ld, obias());
    swap_chunk(&O[8 * K + 8], pd + K * 128 + 128, ps + K * 128 + 128, ld, obias());
    wg_fence();
    wgmma_ss_n128_t0(S, desc64(dQ), koff(K), desc64(dK), koff(K), 1);
    wgmma_ss_n128_t0(S, desc64(dQ), koff(K + 1), desc64(dK), koff(K + 1), 1);
    if constexpr (K < 14) {
        sched_fence<10 + K>(opaque);
        swap_steps<K + 2>(O, S, dQ, dK, pd, ps, ld, opaque);
    }
}

__device__ __forceinline__ void attn_tile(float (&O)[128], float& m0, float& m1, float& l0, float& l1, const uint32_t sb,
                                          const uint32_t dQ, const uint32_t dK0, const uint32_t dV0, const int it, const bool first,
                                          const bool last, const bool shrt, const bool sw, const int slot, const int seed, const int out, const float off,
                                          const int wg, const bool leader, const int opaque) {
    const uint32_t st = it & 1;
    float S[64];
    const float t0 = shrt ? -1e30f : -m0, t1 = shrt ? -1e30f : -m1;
#pragma unroll
    for (int i = 0; i < 64; i += 4) { S[i] = S[i + 1] = i < 56 ? -m0 : t0; S[i + 2] = S[i + 3] = i < 56 ? -m1 : t1; }
    fence_regs(S);
    mbar_wait(sb + SM_BAR + B_FULL + 8 * st, (it >> 1) & 1);
    const uint32_t dK = dK0 + st * (STAGE_B >> 4), dV = dV0 + st * (STAGE_B >> 4);
    bar_sync(1 + wg, 256);
    if (sw) {
        const int t = threadIdx.x & 127;
        uint4* pd = (uint4*)(g_part + slot * PART_BYTES + wg * 32768) + t;
        const uint4* ps = (const uint4*)(g_part + seed * PART_BYTES + wg * 32768) + t;
        swap_steps<0>(O, S, dQ, dK, pd, ps, !first, opaque);
        wg_commit();
        bar_arrive(2 - wg, 256);
        __syncwarp();
        if ((t & 31) == 0) mbar_arrive(sb + SM_BAR + B_SIG + 8 * wg);
        if (!first) {
#pragma unroll
            for (int kk = 0; kk < 16; kk++) unpack_chunk(&O[8 * kk], obias());
        }
    } else {
        if (!shrt) {
            wg_fence();
#pragma unroll
            for (int kk = 0; kk < 16; kk++) wgmma_ss_n128_t0(S, desc64(dQ), koff(kk), desc64(dK), koff(kk), 1);
            wg_commit();
        } else {
            wg_fence();
#pragma unroll
            for (int kk = 0; kk < 16; kk++) wgmma_ss_n112_t0(S, desc64(dQ), koff(kk), desc64(dK), koff(kk), 1);
            wg_commit();
        }
        bar_arrive(2 - wg, 256);
    }
    if (first) {
#pragma unroll
        for (int i = 0; i < 128; i++) asm volatile("mov.b32 %0, %1;" : "+f"(O[i]) : "f"(obias()));
    }
    wg_wait0();
    fence_regs(S);
    if (last && leader) mbar_arrive(sb + SM_BAR + B_QEMPTY + 8 * wg);
    uint32_t u0a = min(__float_as_uint(S[0]), __float_as_uint(S[1])), u1a = min(__float_as_uint(S[2]), __float_as_uint(S[3]));
    uint32_t u0b = min(__float_as_uint(S[4]), __float_as_uint(S[5])), u1b = min(__float_as_uint(S[6]), __float_as_uint(S[7]));
#pragma unroll
    for (int i = 8; i < 64; i += 8) {
        u0a = __vimin3_u32(u0a, __float_as_uint(S[i]), __float_as_uint(S[i + 1]));
        u1a = __vimin3_u32(u1a, __float_as_uint(S[i + 2]), __float_as_uint(S[i + 3]));
        u0b = __vimin3_u32(u0b, __float_as_uint(S[i + 4]), __float_as_uint(S[i + 5]));
        u1b = __vimin3_u32(u1b, __float_as_uint(S[i + 6]), __float_as_uint(S[i + 7]));
    }
    const uint32_t u0 = min(u0a, u0b), u1 = min(u1a, u1b), um = min(u0, u1);
    if (__any_sync(0xffffffffu, um < __float_as_uint(THR - OFF)) || first) {
        float d0 = __uint_as_float(u0), d1 = __uint_as_float(u1);
        if (__any_sync(0xffffffffu, (int)um >= 0)) {
            d0 = fmaxf(S[0], S[1]); d1 = fmaxf(S[2], S[3]);
#pragma unroll
            for (int i = 4; i < 64; i += 4) { d0 = fmaxf(d0, fmaxf(S[i], S[i + 1])); d1 = fmaxf(d1, fmaxf(S[i + 2], S[i + 3])); }
        }
        d0 = ceilf(quad_max(d0)) + off; d1 = ceilf(quad_max(d1)) + off;
        if (!first) {
            d0 = fmaxf(d0, 0.f); d1 = fmaxf(d1, 0.f);
            const float a0 = ex2(-d0), a1 = ex2(-d1);
            l0 *= a0; l1 *= a1;
            rescale(O, a0, a1);
        }
        m0 += d0; m1 += d1;
#pragma unroll
        for (int i = 0; i < 64; i += 4) { S[i] -= d0; S[i + 1] -= d0; S[i + 2] -= d1; S[i + 3] -= d1; }
    }
    uint32_t P[32];
    fence_regs(O);
    exp_steps<0, 3>(S, P, l0, l1);
    sched_fence<1>(opaque);
    bar_sync(1 + wg, 256);
    pv_steps<0, 3>(O, P, dV);
    sched_fence<2>(opaque);
    exp_steps<3, 5>(S, P, l0, l1);
    pv_steps<3, 5>(O, P, dV);
    sched_fence<3>(opaque);
    exp_steps<5, 6>(S, P, l0, l1);
    pv_steps<5, 6>(O, P, dV);
    sched_fence<4>(opaque);
    exp_steps<6, 7>(S, P, l0, l1);
    pv_steps<6, 7>(O, P, dV);
    wg_commit();
    if (!shrt) {
        exp_steps<7, 8>(S, P, l0, l1);
        pv_steps<7, 8>(O, P, dV);
        wg_commit();
    }
    bar_arrive(2 - wg, 256);
    if (last) {
        l0 = quad_sum(l0); l1 = quad_sum(l1);
        if (out != 0xFF && (threadIdx.x & 3) == 0)
            __stcg((float4*)at(g_part + out * PART_BYTES + 65536 + wg * 1024, (threadIdx.x & 127) << 2), make_float4(m0, m1, l0, l1));
    }
    wg_wait0();
    fence_regs(O);
    if (leader) mbar_arrive(sb + SM_BAR + B_EMPTY + 8 * st);
}

__device__ __forceinline__ void load2(uint32_t dst, const uint8_t* src, uint32_t bytes, uint32_t bar) {
    if (elect_one()) {
        mbar_expect_tx(bar, bytes);
        bulk_g2s(dst, src, bytes >> 1, bar);
        bulk_g2s(dst + (bytes >> 1), src + (bytes >> 1), bytes >> 1, bar);
    }
}
__device__ __forceinline__ void store_pieces(uint8_t* dst, uint32_t src, uint32_t bytes) {
#pragma unroll 1
    for (uint32_t o = 0; o < bytes; o += 16384) {
        if (elect_one()) bulk_s2g(dst + o, src + o, min(bytes - o, 16384u));
        bulk_commit();
        bulk_wait_all();
    }
    fence_async_global();
    __syncwarp();
}
__device__ __forceinline__ void timer_edge(uint32_t& c, uint32_t& g) {
    uint32_t g0;
    asm volatile("mov.u32 %0, %globaltimer_lo;" : "=r"(g0));
#pragma unroll 1
    for (int i = 0; i < 256; i++) {
        asm volatile("mov.u32 %0, %globaltimer_lo;" : "=r"(g));
        if (g != g0) break;
    }
    asm volatile("mov.u32 %0, %clock;" : "=r"(c));
}
__device__ __forceinline__ void align_clock() {
    uint32_t c0, c;
    asm volatile("mov.u32 %0, %clock;" : "=r"(c0));
    do { asm volatile("mov.u32 %0, %clock;" : "=r"(c)); } while ((c ^ c0) < 1024);
}
__device__ __forceinline__ void adjust_ranges(const uint32_t* sp, int role, const float (&base)[4], uint32_t& sa, uint32_t& sc) {
    uint32_t v0, v1, v2, v3, v4;
    asm volatile("{\n.reg .pred p;\n.reg .u32 c, m;\nmov.u32 c, 0;\n"
        "LAB_SP:\n"
        "ld.volatile.global.v4.u32 {%0, %1, %2, %3}, [%5];\n"
        "ld.volatile.global.u32 %4, [%5 + 16];\n"
        "min.u32 m, %0, %1;\nmin.u32 m, m, %2;\nmin.u32 m, m, %3;\nmin.u32 m, m, %4;\n"
        "setp.ne.u32 p, m, 0;\n"
        "@p bra LAB_SPD;\n"
        "add.u32 c, c, 1;\n"
        "setp.lt.u32 p, c, 8388608;\n"
        "@p bra LAB_SP;\n"
        "trap;\n"
        "LAB_SPD:\n}\n" : "=r"(v0), "=r"(v1), "=r"(v2), "=r"(v3), "=r"(v4) : "l"(sp) : "memory");
    auto dt = [&](uint32_t v) { return (float)((int)((v - v0) << 14) >> 14); };
    const float k = GAIN * 5.f * rcp((float)((v0 >> 18) + (v1 >> 18) + (v2 >> 18) + (v3 >> 18) + (v4 >> 18)));
    const float c = -GAIN + (dt(v1) + dt(v2) + dt(v3) + dt(v4)) * (1.f / 1555.f);
    auto adj = [&](uint32_t v) { return fmaxf(-8.f, fminf(8.f, (float)(v >> 18) * k - dt(v) * (1.f / 311.f) + c)); };
    const int r0 = __float2int_rn(base[0] + adj(v0)), r1 = __float2int_rn(base[1] + adj(v1)), r2 = __float2int_rn(base[2] + adj(v2));
    const int da = __float2int_rn(0.5f * ((float)(3 * N16 - r0 - r1 - r2) - base[3] + adj(v3) - adj(v4)));
    const int cut = min(r1 + da - (N16 - r0), N16 - NFIX * 8 - 42);
    const int s0 = role == 3 ? r0 : role == 4 ? cut : 0, e0 = role == 0 ? r0 : role == 1 ? r1 : role == 2 ? r2 : N16;
    const int s1 = role == 3 ? r1 : r2, e1 = role == 3 ? cut : N16;
    sa = (sa & 0xFF) | s0 << 8 | (e0 - s0) << 20;
    sc = (sc & 0xFF) | s1 << 8 | (e1 - s1) << 20;
}
__device__ __forceinline__ void fetch_operand(uint32_t sb, uint32_t hdr, bool owner, int z) {
    const uint32_t bar = sb + SM_BAR + B_GO + 8 * (z & 1), dst = sb + (z == 0 ? SM_X : SM_Q);
    const uint8_t* src = g_agg + ((hdr >> 24) + z) * 32768;
    if (owner) {
        const int in = (hdr >> 16) & 0xFF;
        poll_ge(g_sync + F_P + 2 * in + z, 1);
        fence_async_global();
        src = g_part + in * PART_BYTES + z * 32768;
        if (elect_one()) {
            asm volatile("mbarrier.expect_tx.relaxed.cta.shared::cta.b64 [%0], 512;" :: "r"(bar) : "memory");
            bulk_g2s(sb + SM_PAD + z * 1024, g_part + in * PART_BYTES + 65536 + z * 1024, 512, bar);
        }
    }
    load2(dst, src, 32768, bar);
}

__global__ void __launch_bounds__(384, 1)
graphgps_kernel(const uint8_t* __restrict__ x, const int* __restrict__ src,
                const int* __restrict__ dst, const uint16_t* __restrict__ deg_inv, const uint8_t* __restrict__ w_msg,
                const uint8_t* __restrict__ wq, const uint8_t* __restrict__ wk, const uint8_t* __restrict__ wv,
                const uint8_t* __restrict__ w_out, uint8_t* __restrict__ out,
                const __grid_constant__ CUtensorMap out_map, const __grid_constant__ Plan plan) {
    extern __shared__ __align__(1024) uint8_t smem_raw[];
    const uint32_t sb = smem_u32(smem_raw);
    const int tid = threadIdx.x, lane = tid & 31, b = blockIdx.x;
    if (tid == 0 && b < 128) {
        asm volatile("cp.async.bulk.prefetch.L2.global [%0], 1024;" :: "l"(wq + b * 1024) : "memory");
        asm volatile("cp.async.bulk.prefetch.L2.global [%0], 1024;" :: "l"(wk + b * 1024) : "memory");
    }
    if (tid == 32 && b < 128) {
        asm volatile("cp.async.bulk.prefetch.L2.global [%0], 1024;" :: "l"(w_out + b * 1024) : "memory");
        asm volatile("cp.async.bulk.prefetch.L2.global [%0], 1024;" :: "l"(wv + b * 1024) : "memory");
        asm volatile("cp.async.bulk.prefetch.L2.global [%0], 1024;" :: "l"(w_msg + b * 1024) : "memory");
    }
    const int wid = __shfl_sync(0xffffffffu, tid >> 5, 0), wg = wid >> 2, warp = wid & 3;
    const uint32_t hdr = plan.c[b].hdr, slots = plan.c[b].slots;
    const int nseg = hdr & 15;
    const bool owner = (slots & 0xFF) == 0xFF;
    const int qt0 = plan.c[b].seg[0] & 0xFF;
    const bool diag = owner && qt0 < NQT - 1;
    const uint32_t sH = sb + (diag ? SM_KV : SM_Q);
    const int qrow0 = min(qt0 * 128, N_NODES - 128);

    const uint32_t pb = plan.c[b].ptile & 0xFFFF, ptype = pb >> 5, pmt = (pb >> 3) & 3, pnt = pb & 7;
    const uint32_t sP = sb + SM_KV + STAGE_B;
    if (wg == 2 && ptype < 3) {
        const int t = tid - 256;
        const uint32_t dk = sP + (t & 8) * 128 + (t >> 4) * 128 + (((t ^ (t >> 4)) & 7) << 4), sk = (t >> 4) * 512 + (t & 15) * 16;
        uint32_t d = ptype ? sP + 32768 + (t >> 2) * 128 + (((t & 3) ^ ((t >> 2) & 7)) << 4) : dk + 32768;
        const uint8_t* p = ptype ? w_out + pnt * 64 + (t >> 2) * 512 + (t & 3) * 16 : wk + pnt * 16384 + sk;
        const uint32_t dd = ptype ? 4096 : 2048, ds = ptype ? 16384 : 256, dp = ptype ? 32768 : 4096;
#pragma unroll 1
        for (int g = 0; g < 4; g++, d += 2 * dd, p += dp) { cp_async16(d, p); cp_async16(d + dd, p + ds); }
        p = (ptype == 0 ? wq : ptype == 1 ? wv : w_msg) + pmt * 32768 + sk;
        d = dk;
#pragma unroll 1
        for (int g = 0; g < 8; g++, d += 4096, p += 4096) { cp_async16(d, p); cp_async16(d + 2048, p + 256); }
    }
    if (wid == 4 && elect_one()) {
#pragma unroll
        for (uint32_t o = 0; o < NBAR * 8; o += 8)
            mbar_init(sb + SM_BAR + o, (o & ~8u) == B_EMPTY ? 2 : (o & ~8u) == B_SIG || o == B_ZE ? 4 : 1);
        asm volatile("fence.mbarrier_init.release.cluster;" ::: "memory");
        fence_async_smem();
    }
    __syncthreads();

    if (wg == 2) {
        if (ptype < 3) {
            asm volatile("cp.async.wait_all;" ::: "memory");
            fence_async_smem();
            bar_sync(5, 128);
            float acc[16];
#pragma unroll
            for (int j = 0; j < 16; j++) acc[j] = 0.f;
            const uint32_t dL = make_desc(sP, 16);
            if (ptype == 0) {
#pragma unroll 1
                for (int c = 0; c < 4; c++) {
                    wg_fence();
#pragma unroll
                    for (int kk = 0; kk < 4; kk++) wgmma_ss_n32_t0(acc, desc64(dL + c * 64), kk * 2, desc64(dL + c * 64), 2048 + kk * 2, 1);
                    wg_commit();
                }
            } else {
#pragma unroll 1
                for (int c = 0; c < 4; c++) {
                    wg_fence();
#pragma unroll
                    for (int kk = 0; kk < 4; kk++) wgmma_ss_n32_t1(acc, desc64(dL + c * 64), kk * 2, desc64(dL + c * 512, 1024), 2048 + kk * 128, 1);
                    wg_commit();
                }
            }
            wg_wait0();
            fence_regs(acc);
            const float sc = ptype ? 1.f / HS : 1.4426950408889634f / 16.f / (HS * HS);
            uint8_t* dw = g_w + ptype * 131072 + (ptype ? (pnt >> 2) * 65536 + (pnt & 2) * 512 : (pnt >> 1) * 1024);
            const uint32_t sT = sP + warp * 8192;
#pragma unroll
            for (int hh = 0; hh < 2; hh++)
                stsm4(sT + hh * 1024 + (lane & 7) * 80 + (lane >> 3) * 16, pack_bf16(acc[2 * hh] * sc, acc[2 * hh + 1] * sc), pack_bf16(acc[4 + 2 * hh] * sc, acc[5 + 2 * hh] * sc),
                      pack_bf16(acc[8 + 2 * hh] * sc, acc[9 + 2 * hh] * sc), pack_bf16(acc[12 + 2 * hh] * sc, acc[13 + 2 * hh] * sc));
            __syncwarp();
#pragma unroll
            for (int hh = 0; hh < 2; hh++) {
                uint32_t r = pmt * 64 + warp * 16 + hh * 8 + (lane >> 2);
                if (ptype == 2) r = (r & ~31) | ((r & 6) << 2) | ((r >> 2) & 6) | (r & 1);
                *(uint4*)(dw + (r >> 3) * (ptype ? 2048 : 4096) + (r & 7) * 128 + ((((pnt & 1) * 4 + (lane & 3)) ^ (r & 7)) << 4)) =
                    lds128(sT + hh * 1024 + (lane >> 2) * 80 + (lane & 3) * 16);
            }
            fence_async_smem();
            bar_sync(5, 128);
            if (warp == 1) {
                signal_add(g_sync + (ptype == 0 ? C_A : C_W));
                if (ptype == 0 && !owner && lane == 0) mbar_arrive(sb + SM_BAR + B_HSIG);
            }
        }
        asm volatile("setmaxnreg.dec.sync.aligned.u32 56;");
        if (warp == 0) {
            const uint32_t bb = sb + SM_BAR;
            poll_ge(g_sync + C_A, 32);
            fence_async_global();
            load2(sb + (diag ? SM_Q : SM_KV), g_w, 32768, bb + B_T0);
            load2(sb + (diag ? SM_Q : SM_KV) + 32768, g_w + 32768, 32768, bb + B_FULL);
            load2(sb + SM_KV + STAGE_B, g_w + 65536, 65536, bb + B_FULL + 8);
            const uint32_t grp = plan.c[b].ptile >> 16, in = (hdr >> 16) & 0xFF;
            const int nfix = grp == 0xFFFF ? 0 : NFIX;
            int it = 2, it_end = 1 << 20;
            uint32_t o = 0, tc = 0, tg = 0;
#pragma unroll 1
            for (int i = -1; i < nseg; i++) {
                if (i == 0) {
                    uint32_t sa = plan.c[b].seg[0], sc = plan.c[b].seg[1];
                    const uint32_t sd = plan.c[b].seg[2], se = plan.c[b].seg[3];
                    if (nfix) adjust_ranges(g_sync + F_S + (grp & ~7), grp & 7, plan.base, sa, sc);
                    sa -= nfix * 8 << 20;
                    asm volatile("st.shared.v4.u32 [%0], {%1, %2, %3, %4};" :: "r"(bb + S_DYN), "r"(sa), "r"(sc), "r"(sd), "r"(se) : "memory");
                    if (elect_one()) mbar_arrive(bb + B_PLAN);
                    it_end = it + (((sa >> 20) + 7) >> 3) + (owner ? 0 : ((sc >> 20) + 7) >> 3) + (((sd >> 20) + 7) >> 3) + (((se >> 20) + 7) >> 3);
                    it_end = __shfl_sync(0xffffffffu, it_end, 0);
                }
                const uint32_t sg = i < 0 ? plan.c[b].seg[0] : __shfl_sync(0xffffffffu, lds32(bb + S_DYN + 4 * i), 0);
                const int qt = sg & 0xFF, len = i < 0 ? nfix * 8 : sg >> 20, n2 = -len & 7, nt = (len + n2) >> 3;
                const int ts = nt - n2 - (nt - n2 >= 2);
                const uint32_t sw = qt < NQT - 1 ? qt : 0;
                if (!owner && i != 0) o = (((sg >> 8) & 0xFFF) + (sg >> 20)) * 8192;
#pragma unroll 1
                for (int t = 0; t < nt; t++) {
                    const uint32_t bytes = (uint32_t)(t - ts) < n2 ? 57344 : 65536;
                    if (!owner) o -= bytes;
                    const uint32_t ba = o >> 16, na = (o & 65535) + bytes > 65536 ? 65536 - (o & 65535) : 32768, bc = (o + na) >> 16;
                    const uint32_t pa = ba == 0 ? sw : ba == sw ? 0 : ba, pc = bc == 0 ? sw : bc == sw ? 0 : bc;
                    const uint32_t st = it & 1, full = bb + B_FULL + 8 * st, d = sb + SM_KV + st * STAGE_B;
                    const bool own = it == 2 && diag;
                    if (it < 4 && !own) {
                        const bool urgent = it == 2 && o >= (N_NODES - 128) * 512 && sw != NQT - 2;
                        poll_ge(g_sync + (urgent ? C_U : C_H), urgent ? 1 : NQT);
                        fence_async_global();
                    }
                    if (it == 4 && owner) mbar_wait(bb + B_HSIG, 0);
                    mbar_wait(bb + B_EMPTY + 8 * st, ((it >> 1) & 1) ^ 1);
                    if (it > 4 && it != NFIX && (i <= 0 || t > 1)) align_clock();
                    if (elect_one()) {
                        mbar_expect_tx(full, own ? 0 : bytes);
                        if (!own) {
                            bulk_g2s(d, g_h + pa * 65536 + (o & 65535), na, full);
                            bulk_g2s(d + na, g_h + pc * 65536 + ((o + na) & 65535), bytes - na, full);
                        }
                        if (it == 4) mbar_arrive(bb + B_T0);
                        if (it == min(GATH, it_end - 8)) mbar_arrive(bb + B_GATH);
                        if (it + 1 == max(it_end - LATE, 3)) mbar_arrive(bb + B_LATE);
                    }
                    it++;
                    if (owner) o += bytes;
                    if (i < 0 && (it == 5 || it == NFIX + 1)) {
                        uint32_t c, g;
                        timer_edge(c, g);
                        const uint32_t rate = min(__float2uint_rn(__fdividef((c - tc) * 4096.f, g - tg)), 16382u) + 1;
                        if (it != 5 && lane == 0) *(volatile uint32_t*)(g_sync + F_S + grp) = rate << 18 | (g & 0x3FFFF);
                        tc = c; tg = g;
                    }
                    if (i > 0 && t == 0) {
                        poll_ge(g_sync + F_Q + qt, 1);
                        if (i == nseg - 1 && in != 0xFF) poll_ge(g_sync + F_P + 2 * in + 1, 1);
                        fence_async_global();
#pragma unroll 1
                        for (int w = 0; w < 2; w++) {
                            mbar_wait(bb + B_QEMPTY + 8 * w, (i - 1) & 1);
                            if (i == nseg - 1 && in != 0xFF && elect_one()) {
                                asm volatile("mbarrier.expect_tx.relaxed.cta.shared::cta.b64 [%0], 512;" :: "r"(bb + B_QFULL + 8 * w) : "memory");
                                bulk_g2s(sb + SM_PAD + w * 1024, g_part + in * PART_BYTES + 65536 + w * 1024, 512, bb + B_QFULL + 8 * w);
                            }
                            load2(sb + SM_Q + w * 32768, g_q + qt * 65536 + w * 32768, 32768, bb + B_QFULL + 8 * w);
                        }
                    }
                    if (i > 0 && t == 1) {
                        uint32_t* f = g_sync + F_P + 2 * ((slots >> (8 * (i - 1))) & 0xFF);
                        mbar_wait(bb + B_SIG, (i - 1) & 1);
                        mbar_wait(bb + B_SIG + 8, (i - 1) & 1);
                        fence_gpu();
                        if (lane < 2) red_add(f + lane);
                    }
                }
            }
            const uint8_t* W = g_w + (owner ? 131072 : 262144);
            const uint32_t ph = (nseg - 1) & 1, st = it & 1;
            asm volatile("prefetch.tensormap [%0];" :: "l"(&out_map) : "memory");
            poll_ge(g_sync + C_W, 64);
            fence_async_global();
            mbar_wait(bb + B_EMPTY + 8 * st, ((it >> 1) & 1) ^ 1);
            load2(sb + SM_KV + st * STAGE_B, W, 65536, bb + B_FULL + 8 * st);
            if (owner) mbar_wait(bb + B_LATE, 1);
            else { poll_ge(g_sync + C_Z, gridDim.x); fence_async_global(); }
#pragma unroll 1
            for (int w = 0; w < 2; w++) {
                fetch_operand(sb, hdr, owner, w);
                mbar_wait(bb + B_QEMPTY + 8 * w, ph);
            }
            load2(sb + SM_Q + 32768, W + 65536, 32768, bb + B_QFULL + 8);
            if (owner) poll_ge(g_sync + C_Z, gridDim.x);
#pragma unroll 1
            for (int w = 0; w < 2; w++) {
                if (!owner) {
                    mbar_wait(bb + B_SIG + 8 * w, ph);
                    signal_add(g_sync + F_P + 2 * ((slots >> (8 * (nseg - 1))) & 0xFF) + w);
                }
                if (w == 0) {
                    mbar_wait(bb + B_EMPTY + 8 * (st ^ 1), ((it - 1) >> 1) & 1);
                    load2(sb + SM_KV + (st ^ 1) * STAGE_B + 32768, W + 98304, 32768, bb + B_QFULL);
                }
            }
            if (!owner) {
#pragma unroll 1
                for (int z = 2; z < ((hdr >> 8) & 0xFF); z++) { mbar_wait(bb + B_ZE, z & 1); fetch_operand(sb, hdr, false, z); }
            }
            fence_gpu();
            uint32_t done = 0;
            if (lane == 0) done = atomicAdd(g_sync + C_DONE, 1);
            if (__shfl_sync(0xffffffffu, done, 0) == gridDim.x - 1) {
                fence_gpu();
#pragma unroll 1
                for (int i = lane; i < SYNC_WORDS / 4; i += 32) ((uint4*)g_sync)[i] = make_uint4(0, 0, 0, 0);
            }
        } else {
            if (diag) {
                if (warp == 2) {
                    mbar_wait(sb + SM_BAR + B_PUB, 0);
                    if (elect_one()) bulk_s2g(g_h + qrow0 * 512, sH, qt0 == NQT - 2 ? 8192 : 32768);
#pragma unroll 1
                    for (int g = 9; g < 16; g += 2) mbar_wait(sb + SM_BAR + B_LN + 8 * g, 0);
                    if (qt0 != NQT - 2 && elect_one()) bulk_s2g(g_h + qrow0 * 512 + 32768, sH + 32768, 32768);
                    bulk_commit(); bulk_wait_all(); fence_async_global();
                    __syncwarp();
                    if (lane == 0) mbar_arrive(sb + SM_BAR + B_HSIG);
                    signal_add(g_sync + C_H);
                }
            } else if (owner) {
#pragma unroll 1
                for (int i = warp - 1; i < 16; i += 3) {
                    const int g = (i & 7) * 2 + (i >> 3);
                    mbar_wait(sb + SM_BAR + B_LN + 8 * g, 0);
                    uint4 v[8];
#pragma unroll
                    for (int j = 0; j < 8; j++) v[j] = lds128(sH + g * 4096 + j * 512 + lane * 16);
#pragma unroll
                    for (int j = 0; j < 8; j++) *(uint4*)(g_h + qrow0 * 512 + g * 4096 + j * 512 + lane * 16) = v[j];
                }
                bar_sync(6, 96);
                if (warp == 2) {
                    if (lane == 0) mbar_arrive(sb + SM_BAR + B_HSIG);
                    fence_gpu();
                    if (lane < 2) red_add(g_sync + (lane ? C_U : C_H));
                }
            }
            const int G = gridDim.x, t = tid - 288;
            const uint32_t ipc = plan.ipc, magic = plan.magic, ms = plan.ms, qpc = plan.qpc, cap = ms / 2 - 3;
            const uint32_t sX = sb + SM_X, meta = sX + 24576;
            const uint32_t ib = b * ipc, ni = min(ipc, max(ib, N_NODES) - ib);
            mbar_wait(sb + SM_BAR + B_PUB, 0);
            mbar_wait(sb + SM_BAR + B_T0, 1);
#pragma unroll 1
            for (int j = t; j < G; j += 96) sts32(sX + j * 128, 0);
#pragma unroll 1
            for (uint32_t j = t; j < ni; j += 96) { sts32(meta + j * ms, 0); sts16(meta + j * ms + 4, __ldg((const uint16_t*)at(deg_inv, node_of(ib + j) << 1))); }
            bar_sync(6, 96);
#pragma unroll 1
            for (uint32_t q = b * qpc + t; q < min((b + 1) * qpc, N_EDGES / 4); q += 96) {
                const int4 d4 = __ldcs((const int4*)at(dst, q << 4)), s4 = __ldcs((const int4*)at(src, q << 4));
                const uint32_t dd[4] = {index_of(d4.x), index_of(d4.y), index_of(d4.z), index_of(d4.w)};
                const int ss[4] = {s4.x, s4.y, s4.z, s4.w};
#pragma unroll
                for (int j = 0; j < 4; j++) {
                    const uint32_t slot = sX + (dd[j] * magic >> 22) * 128, k = atoms_inc(slot);
                    if (k < 31) sts32(slot + 4 + 4 * k, dd[j] << 16 | ss[j]);
                    pause();
                }
            }
            bar_sync(6, 96);
#pragma unroll 1
            for (int j = t; j < G * 8; j += 96) {
                *(uint4*)(g_xch + ((j >> 3) * MAXCTA + b) * 128 + (j & 7) * 16) = lds128(sX + j * 16);
                pause();
            }
            fence_async_smem();
            bar_sync(6, 96);
            if (warp == 1) signal_add(g_sync + C_E);
            if (warp == 3 && owner && (hdr & 0x100)) {
                mbar_wait(sb + SM_BAR + B_SIG, 0);
                mbar_wait(sb + SM_BAR + B_SIG + 8, 0);
                store_pieces(g_q + qt0 * 65536, sb + SM_Q, 65536);
                signal_add(g_sync + F_Q + qt0);
            }
            if (warp == 1) {
                poll_ge_slow(g_sync + C_E, G);
                fence_async_global();
                load2(sX, g_xch + b * MAXCTA * 128, G * 128, sb + SM_BAR + B_LN + 8);
            }
            mbar_wait(sb + SM_BAR + B_LN + 8, 1);
            auto add_edge = [&](uint32_t li, uint32_t s) {
                const uint32_t k = atoms_inc(meta + li * ms);
                if (k < cap) sts16(meta + li * ms + 6 + 2 * k, s);
            };
#pragma unroll 1
            for (int j = warp - 1; j < G; j += 3) {
                const uint32_t c = lds32(sX + j * 128), w = lds32(sX + j * 128 + lane * 4);
                if (c < 32) {
                    if (lane - 1u < c) add_edge((w >> 16) - ib, w);
                } else {
#pragma unroll 1
                    for (uint32_t e = j * qpc * 4 + lane; e < min((j + 1) * qpc * 4, N_EDGES); e += 32) {
                        const uint32_t li = index_of(__ldg(dst + e)) - ib;
                        if (li < ni) add_edge(li, __ldg(src + e));
                    }
                }
                __syncwarp();
            }
            bar_sync(6, 96);
            const int i0 = (ni >> 1) * (warp - 1) / 3 * 2, nn = (ni >> 1) * warp / 3 * 2 - i0;
            if (nn > 0) {
                mbar_wait(sb + SM_BAR + B_GATH, 0);
                const uint32_t mw = meta + i0 * ms, lg = lane >> 3, l7 = lane & 7;
                uint32_t sg = sX + (warp - 1) * 8192 + lane * 16, sd = sX + (warp - 1) * 8192 + lg * 512 + l7 * 16;
                const uint8_t* hb = g_h + 2048;
                asm volatile("" : "+l"(hb));
                uint32_t mp = mw + 6 + lg * 2;
                int ii = 0, rem = __shfl_sync(0xffffffffu, min(lds32(mw), cap), 0), flip = 4096;
                int pb = 0, qb = 0, pi = 0;
                uint4 acc = make_uint4(0, 0, 0, 0), keep = acc;
#pragma unroll 1
                for (;;) {
                    const uint32_t s0 = lds16(mp), s1 = lds16(mp + 8);
                    asm volatile("cp.async.wait_group 1;" ::: "memory");
                    __syncwarp();
                    if (pb & 15) {
                        uint4 v = add4(add4(lds128(sg), lds128(sg + 512)), add4(lds128(sg + 1024), lds128(sg + 1536)));
                        if ((pb & 15) > 4) v = add4(v, add4(add4(lds128(sg + 2048), lds128(sg + 2560)), add4(lds128(sg + 3072), lds128(sg + 3584))));
                        acc = add4(acc, v);
                    }
                    __syncwarp();
                    if (rem > 0) {
                        const uint8_t* r = hb + ((s0 * 512 - (s0 & 7) * 368) ^ (l7 << 4));
#pragma unroll
                        for (int q = 0; q < 4; q++) { cp_async16_zfill(sd + q * 128, r + (q - 2) * 1024, lg < rem ? 16 : 0); if (q & 1) pause(); }
                    }
                    if (rem > 4) {
                        const uint8_t* r = hb + ((s1 * 512 - (s1 & 7) * 368) ^ (l7 << 4));
#pragma unroll
                        for (int q = 0; q < 4; q++) { cp_async16_zfill(sd + 2048 + q * 128, r + (q - 2) * 1024, lg + 4 < rem ? 16 : 0); if (q == 1) pause(); }
                    }
                    asm volatile("cp.async.commit_group;" ::: "memory");
                    sg += flip; sd += flip; flip = -flip;
                    if (pb >> 8) {
                        const uint32_t di = lds16(mw + pi * ms + 4) * 0x10001u;
                        const uint4 w = make_uint4(mul_bf16x2(acc.x, di), mul_bf16x2(acc.y, di), mul_bf16x2(acc.z, di), mul_bf16x2(acc.w, di));
                        if (pi & 1) {
                            const int n = node_of(ib + i0 + pi);
                            uint8_t* ap = g_agg + (n >> 6) * 32768 + (lane >> 2) * 4096 + ((n >> 4) & 3) * 512 + (n & 7) * 64 + (lane & 3) * 16;
                            *(uint4*)ap = make_uint4(keep.x, w.x, keep.y, w.y);
                            *(uint4*)(ap + 2048) = make_uint4(keep.z, w.z, keep.w, w.w);
                            if (pi == nn - 1) break;
                        }
                        keep = w;
                        acc = make_uint4(0, 0, 0, 0);
                        pi++;
                    }
                    pb = qb;
                    qb = min(rem, 8);
                    rem -= 8; mp += 16;
                    if (rem <= 0) {
                        qb |= 256;
                        ii = min(ii + 1, nn);
                        mp = mw + ii * ms + 6 + lg * 2;
                        rem = ii < nn ? __shfl_sync(0xffffffffu, min(lds32(mw + ii * ms), cap), 0) : 0;
                    }
                }
                asm volatile("cp.async.wait_all;" ::: "memory");
#pragma unroll 1
                for (int i = 0; i < nn; i++) {
                    if (lds32(mw + i * ms) <= cap) continue;
                    const int n = node_of(ib + i0 + i);
                    float a[8] = {0.f, 0.f, 0.f, 0.f, 0.f, 0.f, 0.f, 0.f};
#pragma unroll 1
                    for (int q = lane; q < N_EDGES / 4; q += 32) {
                        const int4 d4 = __ldg((const int4*)dst + q);
                        uint32_t hit = (d4.x == n) | (d4.y == n) << 1 | (d4.z == n) << 2 | (d4.w == n) << 3;
                        for (uint32_t mk; (mk = __ballot_sync(0xffffffffu, hit)) != 0;) {
                            const int l = __ffs(mk) - 1, e = __shfl_sync(0xffffffffu, q * 4 + __ffs(hit) - 1, l);
                            if (lane == l) hit &= hit - 1;
                            acc_bf16(a, ld_cg16(g_h + sw_unit(__ldg(src + e), lane)));
                        }
                    }
                    uint32_t* ap = (uint32_t*)(g_agg + (n >> 6) * 32768 + (lane >> 2) * 4096 + ((n >> 4) & 3) * 512 + (n & 7) * 64 + (lane & 3) * 16) + (i & 1);
                    const float di = __uint_as_float(lds16(mw + i * ms + 4) << 16);
                    ap[0] = pack_bf16(a[0] * di, a[1] * di); ap[2] = pack_bf16(a[2] * di, a[3] * di);
                    ap[512] = pack_bf16(a[4] * di, a[5] * di); ap[514] = pack_bf16(a[6] * di, a[7] * di);
                }
            }
            bar_sync(6, 96);
            if (warp == 1) {
                const int n1 = ib + ni;
                mbar_wait(sb + SM_BAR + B_LATE, 0);
                fence_async_smem();
                int ph = 1;
#pragma unroll 1
                for (int n = ib; n < n1; n += 64, ph ^= 1) {
                    const uint32_t bytes = min(64, n1 - n) * 512;
                    load2(sb + SM_X, x + n * 512, bytes, sb + SM_BAR + B_LN);
                    mbar_wait(sb + SM_BAR + B_LN, ph);
                    store_pieces(out + n * 512, sb + SM_X, bytes);
                }
                if (lane == 0) mbar_arrive(sb + SM_BAR + B_LATE);
                signal_add(g_sync + C_Z);
            }
        }
    } else {
        const bool leader = (tid & 127) == 0;
        if (wg == 1) bar_arrive(1, 256);
        {
            auto load_x = [&](int w, int g) {
                if (elect_one()) {
                    const uint32_t bar = sb + SM_BAR + B_X + 16 * w + 8 * g;
                    mbar_expect_tx(bar, 4096);
                    bulk_g2s(sH + w * 8192 + g * 4096, x + qrow0 * 512 + w * 8192 + g * 4096, 4096, bar);
                }
            };
            const bool hold = ptype == 0 && !owner;
            if (wg == 1 && hold) mbar_wait(sb + SM_BAR + B_HSIG, 0);
            if (wg == 0 || hold) { load_x(wid, 0); load_x(wid, 1); }
            const int rr = lane >> 3, u = lane & 7;
#pragma unroll 1
            for (int g = 0; g < 2; g++) {
                const uint32_t gb = wid * 8192 + g * 4096;
                float f[2][32], s[2], dm[2];
                mbar_wait(sb + SM_BAR + B_X + 16 * wid + 8 * g, 0);
                if (wg == 0 && !hold) load_x(wid ^ 4, g);
#pragma unroll
                for (int j = 0; j < 2; j++) {
#pragma unroll
                    for (int c = 0; c < 4; c++) {
                        const uint4 v = lds128(sH + gb + (rr + 4 * j) * 512 + c * 128 + u * 16);
                        f[j][8 * c] = bf_lo(v.x); f[j][8 * c + 1] = bf_hi(v.x); f[j][8 * c + 2] = bf_lo(v.y); f[j][8 * c + 3] = bf_hi(v.y);
                        f[j][8 * c + 4] = bf_lo(v.z); f[j][8 * c + 5] = bf_hi(v.z); f[j][8 * c + 6] = bf_lo(v.w); f[j][8 * c + 7] = bf_hi(v.w);
                    }
                    float a0 = 0.f, a1 = 0.f, a2 = 0.f, a3 = 0.f;
#pragma unroll
                    for (int e = 0; e < 32; e += 4) { a0 += f[j][e]; a1 += f[j][e + 1]; a2 += f[j][e + 2]; a3 += f[j][e + 3]; }
                    s[j] = (a0 + a1) + (a2 + a3);
                }
#pragma unroll
                for (int o = 4; o > 0; o >>= 1) { s[0] += __shfl_xor_sync(0xffffffffu, s[0], o); s[1] += __shfl_xor_sync(0xffffffffu, s[1], o); }
#pragma unroll
                for (int j = 0; j < 2; j++) {
                    const float mean = s[j] * (1.f / 256.f);
                    dm[j] = mean - round_bf16(mean);
                    float a0 = 0.f, a1 = 0.f, a2 = 0.f, a3 = 0.f;
#pragma unroll
                    for (int e = 0; e < 32; e += 4) {
                        f[j][e] -= mean; f[j][e + 1] -= mean; f[j][e + 2] -= mean; f[j][e + 3] -= mean;
                        a0 += f[j][e] * f[j][e]; a1 += f[j][e + 1] * f[j][e + 1]; a2 += f[j][e + 2] * f[j][e + 2]; a3 += f[j][e + 3] * f[j][e + 3];
                    }
                    s[j] = (a0 + a1) + (a2 + a3);
                }
#pragma unroll
                for (int o = 4; o > 0; o >>= 1) { s[0] += __shfl_xor_sync(0xffffffffu, s[0], o); s[1] += __shfl_xor_sync(0xffffffffu, s[1], o); }
                __syncwarp();
#pragma unroll
                for (int j = 0; j < 2; j++) {
                    const float rs = HS * rcp(round_bf16(sqrt_approx(round_bf16(round_bf16(s[j] * (1.f / 256.f)) + 1e-5f)))), sh = dm[j] * rs;
                    const uint32_t off = gb + (rr + 4 * j) * 128 + ((u ^ (rr + 4 * j)) << 4);
#pragma unroll
                    for (int c = 0; c < 4; c++) {
                        const uint4 v = make_uint4(pack_bf16(fmaf(f[j][8 * c], rs, sh), fmaf(f[j][8 * c + 1], rs, sh)), pack_bf16(fmaf(f[j][8 * c + 2], rs, sh), fmaf(f[j][8 * c + 3], rs, sh)),
                                                   pack_bf16(fmaf(f[j][8 * c + 4], rs, sh), fmaf(f[j][8 * c + 5], rs, sh)), pack_bf16(fmaf(f[j][8 * c + 6], rs, sh), fmaf(f[j][8 * c + 7], rs, sh)));
                        asm volatile("st.shared.v4.u32 [%0], {%1, %2, %3, %4};" :: "r"(sH + off + c * 1024), "r"(v.x), "r"(v.y), "r"(v.z), "r"(v.w) : "memory");
                    }
                }
                fence_async_smem();
                __syncwarp();
                if (lane == 0) mbar_arrive(sb + SM_BAR + B_LN + 16 * wid + 8 * g);
            }
        }
        asm volatile("setmaxnreg.inc.sync.aligned.u32 224;");
        const uint32_t dQ = make_desc(sb + SM_Q + wg * 32768, 16);
        const uint32_t dK0 = make_desc(sb + SM_KV, 16);
        const uint32_t dV0 = make_desc(sb + SM_KV, 1024);
        float O[128];
        const bool idle = qt0 == NQT - 1 && wid < 7;
        const uint32_t dH = make_desc(sH + wg * 32768, 16), dA0 = make_desc(sb + (diag ? SM_Q : SM_KV), 1024);
        mbar_wait(sb + SM_BAR + B_T0, 0);
        bar_sync(1 + wg, 256);
        if (tid == 0) mbar_arrive(sb + SM_BAR + B_PUB);
#pragma unroll
        for (int kk = 0; kk < 16; kk++) {
            if (kk == 8) wg_commit();
            if (kk == 4 || kk == 8) mbar_wait(sb + SM_BAR + B_FULL + 2 * (kk - 4), 0);
            if (kk == 0 || kk == 4 || kk == 8) wg_fence();
            wgmma_ss_n256_t1(O, desc64(dH), koff(kk), desc64(kk >= 8 ? dV0 + (STAGE_B >> 4) : dA0), (kk & 7) * 512, kk != 0);
        }
        wg_commit();
        bar_arrive(2 - wg, 256);
        asm volatile("wgmma.wait_group.sync.aligned 1;" ::: "memory");
        if (leader) mbar_arrive(sb + SM_BAR + B_EMPTY);
        wg_wait0();
        fence_regs(O);
        if (leader) mbar_arrive(sb + SM_BAR + B_EMPTY + 8);
        {
            if (owner) mbar_wait(sb + SM_BAR + (diag ? B_EMPTY : B_HSIG), 0);
            const uint32_t row = wg * 64 + warp * 16 + (lane & 15);
#pragma unroll
            for (int j = 0; j < 16; j++)
                stsm4(sb + SM_Q + sw_unit(row, 2 * j + (lane >> 4)), pack_bf16(O[8 * j], O[8 * j + 1]), pack_bf16(O[8 * j + 2], O[8 * j + 3]),
                      pack_bf16(O[8 * j + 4], O[8 * j + 5]), pack_bf16(O[8 * j + 6], O[8 * j + 7]));
            if (idle) {
                __syncwarp();
#pragma unroll 1
                for (int j = 0; j < 64; j++) sts32(sb + SM_Q + wid * 8192 + j * 128 + lane * 4, 0);
            }
            fence_async_smem();
            __syncwarp();
            if (owner && lane == 0) mbar_arrive(sb + SM_BAR + B_SIG + 8 * wg);
        }
        const int seed = (hdr >> 16) & 0xFF;
        int it = 2, itf = 2, itw = 0, slot = 0;
        float m0 = OFF, m1 = OFF, l0 = 0.f, l1 = 0.f;
#pragma unroll 1
        for (int i = -1; i < nseg; i++) {
            const int opq = plan.c[b].seg[0];
            const int len = i < 0 ? (plan.c[b].ptile >> 16 == 0xFFFF ? 0 : NFIX * 8)
                                  : __shfl_sync(0xffffffffu, lds32(sb + SM_BAR + S_DYN + 4 * i), 0) >> 20;
            const int n2 = -len & 7, ite = it + ((len + 7) >> 3), its = ite - n2 - (ite - n2 - it >= 2), itl = i < 0 ? 0 : ite - 1;
#pragma unroll 1
            for (; it < ite; it++)
                attn_tile(O, m0, m1, l0, l1, sb, dQ, dK0, dV0, it, it == itf, it == itl, (uint32_t)(it - its) < n2, it == itw, slot, seed,
                          (slots >> (8 * max(i, 0))) & 0xFF, idle && i <= 0 ? 400.f : OFF, wg, leader, opq);
            if (i < 0) { mbar_wait(sb + SM_BAR + B_PLAN, 0); continue; }
            slot = (slots >> (8 * i)) & 0xFF;
            if (i == nseg - 1) break;
            mbar_wait(sb + SM_BAR + B_QFULL + 8 * wg, i & 1);
            itw = it;
            if (i == nseg - 2 && seed != 0xFF) {
                const uint4 s4 = lds128(sb + SM_PAD + wg * 1024 + ((tid & 127) >> 2) * 16);
                m0 = __uint_as_float(s4.x); m1 = __uint_as_float(s4.y); l0 = 0.25f * __uint_as_float(s4.z); l1 = 0.25f * __uint_as_float(s4.w);
            } else {
                m0 = OFF; m1 = OFF; l0 = 0.f; l1 = 0.f;
                itf = it;
            }
        }
        uint32_t A[64];
        const uint32_t stW = it & 1, stS = stW ^ 1;
        uint32_t here;
        uint4 s4;
        asm volatile("{\n.reg .pred o, p, q;\nsetp.ne.u32 o, %9, 0;\nsetp.ne.u32 p, 0, 0;\nsetp.ne.u32 q, 0, 0;\n"
                     "mov.u32 %1, 0;\nmov.u32 %2, 0;\nmov.u32 %3, 0;\nmov.u32 %4, 0;\n"
                     "@o mbarrier.test_wait.parity.shared::cta.b64 p, [%5], %6;\n"
                     "@o mbarrier.test_wait.parity.shared::cta.b64 q, [%7], 0;\n"
                     "and.pred p, p, q;\n"
                     "@p ld.shared.v4.u32 {%1, %2, %3, %4}, [%8];\n"
                     "selp.u32 %0, 1, 0, p;\n}\n"
                     : "=r"(here), "=r"(s4.x), "=r"(s4.y), "=r"(s4.z), "=r"(s4.w)
                     : "r"(sb + SM_BAR + B_FULL + 8 * stW), "r"((it >> 1) & 1), "r"(sb + SM_BAR + B_GO + 8 * wg),
                       "r"(sb + SM_PAD + wg * 1024 + ((tid & 127) >> 2) * 16), "r"((uint32_t)owner) : "memory");
#pragma unroll
        for (int j = 0; j < 64; j++) A[j] = pack_bf16(O[2 * j] - obias(), O[2 * j + 1] - obias());
#pragma unroll
        for (int j = 0; j < 64; j++) asm volatile("" : "+r"(A[j]) :: "memory");
        const int nz = owner ? 2 : (hdr >> 8) & 0xFF, row0 = owner ? qrow0 : (hdr >> 24) * 64;
        const uint32_t dWa = dV0 + stW * (STAGE_B >> 4), dWb = make_desc(sb + SM_Q + 32768, 1024), dWc = dV0 + stS * (STAGE_B >> 4) + 2048;
        const uint32_t stg = sb + (wg == 0 ? SM_KV + stS * STAGE_B : SM_X) + warp * 4096, stw = (lane & 15) * 128 + (((lane >> 4) ^ (lane & 7)) << 4);
        uint32_t w0 = 0, w1 = 0;
        float r0 = 1.f, r1 = 1.f;
        if (!owner) {
            uint4* pd = (uint4*)(g_part + slot * PART_BYTES + wg * 32768) + (tid & 127);
#pragma unroll
            for (int j = 0; j < 16; j++) __stcg(pd + j * 128, make_uint4(A[4 * j], A[4 * j + 1], A[4 * j + 2], A[4 * j + 3]));
            __syncwarp();
            if (lane == 0) mbar_arrive(sb + SM_BAR + B_SIG + 8 * wg);
        }
        if (!here) {
            mbar_wait(sb + SM_BAR + B_FULL + 8 * stW, (it >> 1) & 1);
            mbar_wait(sb + SM_BAR + B_GO + 8 * wg, 0);
            s4 = lds128(sb + SM_PAD + wg * 1024 + ((tid & 127) >> 2) * 16);
        }
        if (owner) {
            const float a0 = ex2(fminf(m0 - __uint_as_float(s4.x), 100.f)), a1 = ex2(fminf(m1 - __uint_as_float(s4.y), 100.f));
            w0 = pack_bf16(a0, a0); w1 = pack_bf16(a1, a1);
            r0 = rcp(l0 * a0 + __uint_as_float(s4.z));
            r1 = rcp(l1 * a1 + __uint_as_float(s4.w));
        }
#pragma unroll 1
        for (int r = 0; r < nz; r++) {
            const bool split = r == nz - 1 && !(r & 1);
            const int z = split ? r : (r & ~1) + wg, half = split ? wg : r & 1, rb = row0 + z * 64 + warp * 16;
            float Y[64];
            if (!(r & 1) && r) mbar_wait(sb + SM_BAR + B_GO + 8 * (z & 1), (z >> 1) & 1);
            const uint32_t d0 = half ? dWb : dWa, d1 = half ? dWc : dWa + 2048, op = sb + (z == 0 ? SM_X : SM_Q) + (tid & 127) * 16;
            constexpr int TC = 2;
            uint4 u[2][TC];
#pragma unroll
            for (int j = 0; j < TC; j++) u[0][j] = u[1][j] = make_uint4(0, 0, 0, 0);
#pragma unroll
            for (int c = 0; c < 16; c += TC) {
                if (!(r & 1)) {
                    const int p = (c / TC) & 1;
                    if (c == 0) {
#pragma unroll
                        for (int j = 0; j < TC; j++) u[0][j] = lds128(op + j * 2048);
                    }
                    if (c + TC < 16) {
#pragma unroll
                        for (int j = 0; j < TC; j++) u[p ^ 1][j] = lds128(op + (c + TC + j) * 2048);
                    }
#pragma unroll
                    for (int j = 0; j < TC; j++) {
                        const int kk = c + j;
                        A[4 * kk] = fma_bf16x2(A[4 * kk], w0, u[p][j].x); A[4 * kk + 1] = fma_bf16x2(A[4 * kk + 1], w1, u[p][j].y);
                        A[4 * kk + 2] = fma_bf16x2(A[4 * kk + 2], w0, u[p][j].z); A[4 * kk + 3] = fma_bf16x2(A[4 * kk + 3], w1, u[p][j].w);
                    }
                }
                if (c == 0) bar_sync(1 + wg, 256);
                wg_fence();
#pragma unroll
                for (int kk = c; kk < c + TC; kk++)
                    wgmma_rs_n128_t1(Y, A[4 * kk], A[4 * kk + 1], A[4 * kk + 2], A[4 * kk + 3], desc64(kk < 8 ? d0 : d1, 2048), (kk & 7) * 256, kk != 0);
            }
            wg_commit();
            bar_arrive(2 - wg, 256);
            if (!(r & 1) && z != 0 && lane == 0) mbar_arrive(sb + SM_BAR + B_ZE);
            if (r == 0) { mbar_wait(sb + SM_BAR + B_QFULL + 8, (nseg - 1) & 1); mbar_wait(sb + SM_BAR + B_QFULL, (nseg - 1) & 1); }
            asm volatile("cp.async.bulk.wait_group.read 1;" ::: "memory");
            __syncwarp();
            wg_wait0();
            fence_regs(Y);
            const uint32_t sd = stg + (r & 1) * 16384;
#pragma unroll
            for (int c = 0; c < 2; c++) {
#pragma unroll
                for (int j = 4 * c; j < 4 * c + 4; j++)
                    stsm4(sd + (stw ^ ((j & 3) << 5)) + c * 2048, pack_bf16(Y[8 * j] * r0, Y[8 * j + 1] * r0), pack_bf16(Y[8 * j + 2] * r1, Y[8 * j + 3] * r1),
                          pack_bf16(Y[8 * j + 4] * r0, Y[8 * j + 5] * r0), pack_bf16(Y[8 * j + 6] * r1, Y[8 * j + 7] * r1));
                fence_async_smem();
                fence_async_global();
                __syncwarp();
                if (rb < N_NODES && (!owner || rb >= qt0 * 128) && elect_one()) tma_red_add(&out_map, sd + c * 2048, rb, 128 * half + 64 * c);
            }
            bulk_commit();
        }
        if (wg == 0) bar_sync(1, 256);
        bulk_wait_all();
    }
}

bool seg_ok(int len) { return len >= 22 && len >= 7 * (-len & 7) + 8; }

bool fill_plan(Plan& pl, int G, const int* ra, const int* cut, const int* zc) {
    const int nd = G - NQT;
    int in[NQT], pub[NQT];
    for (int t = 0; t < NQT; t++) { in[t] = -1; pub[t] = 0; }
    int pos = 0, slot = 0, t = 0, t0 = 0;
    for (int d = 0; d < nd; d++) {
        CtaPlan& c = pl.c[NQT + d];
        int ns = 0, init = 0xFF;
        c.slots = 0;
        for (int i = 0; i < MAXSEG; i++) c.seg[i] = 0;
        while (pos < cut[d]) {
            const int t1 = t0 + N16 - ra[t], end = cut[d] < t1 ? cut[d] : t1;
            if (ns == MAXSEG || slot + 1 >= MAXSLOT || !seg_ok(end - pos)) return false;
            if (pos == t0) {
                in[t] = slot;
                if (end < t1) { if (ns == 0) return false; init = slot + 1; }
            } else if (end < t1) return false;
            if (ns > 0) pub[t] = 1;
            c.seg[ns] = t | (ra[t] + pos - t0) << 8 | (end - pos) << 20;
            c.slots |= slot << (8 * ns);
            ns++; slot++; pos = end;
            if (pos == t1) { t0 = t1; t++; }
        }
        const int z0 = d ? zc[d - 1] : 0;
        c.hdr = ns | (zc[d] - z0) << 8 | init << 16 | z0 << 24;
    }
    for (int k = 0; k < NQT; k++) {
        CtaPlan& c = pl.c[k];
        if (in[k] < 0 || !seg_ok(ra[k])) return false;
        c.hdr = 1 | pub[k] << 8 | in[k] << 16;
        c.slots = 0xFF;
        c.seg[0] = k | ra[k] << 20;
        for (int i = 1; i < MAXSEG; i++) c.seg[i] = 0;
    }
    return true;
}

bool build_plan(Plan& pl, int G, int r) {
    const int nd = G - NQT, L = N16 - r, total = NQT * L;
    int ra[NQT], cut[MAXCTA], zc[MAXCTA];
    for (int t = 0; t < NQT; t++) ra[t] = r;
    for (int d = 0; d < nd; d++) {
        const int end = (int)(((long long)total * (d + 1) + nd / 2) / nd);
        cut[d] = end;
        for (int k = 0; k < 2 * L; k++) {
            const int c = end + (k & 1 ? -(k + 1) / 2 : k / 2), off = c % L;
            if (off == 0 || (seg_ok(off) && seg_ok(L - off))) { cut[d] = c; break; }
        }
        zc[d] = NZT * (d + 1) / nd;
    }
    return fill_plan(pl, G, ra, cut, zc);
}

constexpr float B0 = 380.6f;
constexpr float B1 = 380.2f;
constexpr float B3 = 3.f;
constexpr int ROT = 8;
constexpr int ZREST = 4;
constexpr int DYN = 1;
void build_plan_132(Plan& pl, int r0, int r1, int skew, int zrest) {
    int ra[NQT], cut[53], zc[53], pos = 0;
    for (int t = 0; t < NQT; t++) ra[t] = t % 3 ? r1 : r0;
    ra[NQT - 1] = 344;
    for (int g = 0; g < 26; g++) {
        const int tot = 3 * N16 - r0 - 2 * r1;
        cut[2 * g] = pos + (tot - skew) / 2;
        cut[2 * g + 1] = pos += tot;
    }
    cut[52] = pos + N16 - ra[NQT - 1];
    for (int d = 0; d < 52; d++) zc[d] = (NZT - zrest) * (d + 1) / 52;
    zc[52] = NZT;
    fill_plan(pl, 132, ra, cut, zc);
    pl.base[0] = B0; pl.base[1] = pl.base[2] = B1; pl.base[3] = B3;
}

bool make_plan(Plan& plan, int G, int* order) {
    Plan pl = {};
    if (G == 132) build_plan_132(pl, 381, 381, 2, ZREST);
    else {
        int ra = (NQT * N16 + (G - NQT) * 12 + G / 2) / G;
        while (G >= 96 && ra < N16 && !build_plan(pl, G, ra)) ra++;
        if (G < 96 || ra >= N16) return false;
    }
    for (int i = 0, o = 0, d = 0; i < G; i++) {
        if (d < G - NQT && d * G <= i * (G - NQT)) order[i] = NQT + d++;
        else order[i] = (NQT - 1 + o++) % NQT;
    }
    if (G == 132) {
        order[0] = NQT - 1; order[1] = 131;
        for (int g = 0; g < 26; g++)
            for (int k = 0; k < 5; k++) {
                const int role = (k + g / ROT * 2) % 5;
                order[2 + k * 26 + g] = role < 3 ? 3 * g + role : NQT + 2 * g + role - 3;
            }
    }
    for (int j = 0; j < G; j++) {
        const int p = j >= NQT ? j - NQT : G - NQT + j;
        const int grp = !DYN || G != 132 || j == NQT - 1 || j == 131 ? 0xFFFF : j < NQT ? j / 3 * 8 + j % 3 : (j - NQT) / 2 * 8 + 3 + (j - NQT) % 2;
        pl.c[j].ptile = p | grp << 16;
    }
    for (int i = 0; i < 4; i++) plan.base[i] = pl.base[i];
    plan.ipc = 2 * ((N_NODES / 2 + G - 1) / G);
    plan.magic = ((1u << 22) + plan.ipc - 1) / plan.ipc;
    plan.ms = 8192 / (plan.ipc + 1) < 96 ? 8192 / (plan.ipc + 1) & ~3u : 96;
    plan.qpc = (N_EDGES / 4 + G - 1) / G;
    for (int i = 0; i < G; i++) plan.c[i] = pl.c[order[i]];
    return true;
}

}

extern "C" void kernel_launch(void* const* d_in, const int* in_sizes, int n_in, void* d_out, int out_size) {
    static Plan plan;
    static int grid = 0;
    static decltype(&cuTensorMapEncodeTiled) encode = nullptr;
    if (grid == 0) {
        int dev = 0, sms = 0;
        cudaDriverEntryPointQueryResult qr;
        cudaGetDriverEntryPoint("cuTensorMapEncodeTiled", (void**)&encode, cudaEnableDefault, &qr);
        cudaGetDevice(&dev);
        cudaDeviceGetAttribute(&sms, cudaDevAttrMultiProcessorCount, dev);
        cudaFuncSetAttribute(graphgps_kernel, cudaFuncAttributeMaxDynamicSharedMemorySize, SMEM_BYTES);
        grid = sms < MAXCTA ? sms : MAXCTA;
        int order[MAXCTA];
        if (!make_plan(plan, grid, order) || !encode) grid = -1;
    }
    if (grid < 0) return;
    CUtensorMap out_map;
    const cuuint64_t dims[2] = {256, N_NODES}, strides[1] = {512};
    const cuuint32_t box[2] = {64, 16}, estr[2] = {1, 1};
    encode(&out_map, CU_TENSOR_MAP_DATA_TYPE_BFLOAT16, 2, d_out, dims, strides, box, estr, CU_TENSOR_MAP_INTERLEAVE_NONE,
           CU_TENSOR_MAP_SWIZZLE_128B, CU_TENSOR_MAP_L2_PROMOTION_NONE, CU_TENSOR_MAP_FLOAT_OOB_FILL_NONE);
    graphgps_kernel<<<grid, 384, SMEM_BYTES>>>((const uint8_t*)d_in[0], (const int*)d_in[1], (const int*)d_in[2],
                                               (const uint16_t*)d_in[3], (const uint8_t*)d_in[4], (const uint8_t*)d_in[5],
                                               (const uint8_t*)d_in[6], (const uint8_t*)d_in[7], (const uint8_t*)d_in[8], (uint8_t*)d_out,
                                               out_map, plan);
}
```
